```python
import torch

def _softmax(x, axis=-1):
    return torch.softmax(x, dim=axis)

def _gelu(x):
    return torch.nn.functional.gelu(x, approximate='tanh')

def _silu(x):
    return torch.nn.functional.silu(x)

def _sigmoid(x):
    return torch.sigmoid(x)

def _layernorm(x, axis=-1, eps=1e-05):
    m = x.mean(dim=axis, keepdim=True)
    v = x.var(dim=axis, keepdim=True, unbiased=False)
    return (x - m) / torch.sqrt(v + eps)

def _scatter_add(tgt, idx, src, axis=0):
    return tgt.clone().index_add_(axis, idx, src)

def _segment_sum(src, seg, n):
    out = torch.zeros((n,) + src.shape[1:], dtype=src.dtype)
    return out.index_add_(0, seg, src)

def _pad(x, pw):
    flat = tuple((v for pair in reversed(pw) for v in pair))
    return torch.nn.functional.pad(x, flat)
kernel_name = 'gated_mix__memory_aug_recurrent_mem_tr__swiglu_ffn__prompt'

def setup_inputs():

    _w = lambda a: (lambda t: t.to(torch.bfloat16) if t.is_floating_point() else t)(torch.as_tensor(a))

    def _A_setup():
        B, S, Dm = (1, 2048, 1024)
        H, Dh = (32, 128)
        M, seg = (8, 32)
        seg = min(seg, S)
        S = S // seg * seg
        return {'x': _w((lambda *s: torch.randn(*s, dtype=torch.bfloat16) * 0.05)(B, S, Dm)), 'mem0': _w((lambda *s: torch.randn(*s, dtype=torch.bfloat16) * 0.4)(B, M, Dm)), 'Wq': _w((lambda *s: torch.randn(*s, dtype=torch.bfloat16) * 6.4)(Dm, H, Dh) * Dm ** (-0.5)), 'Wk': _w((lambda *s: torch.randn(*s, dtype=torch.bfloat16) * 6.4)(Dm, H, Dh) * Dm ** (-0.5)), 'Wv': _w((lambda *s: torch.randn(*s, dtype=torch.bfloat16) * 0.4)(Dm, H, Dh) * Dm ** (-0.5)), 'Wo': _w((lambda *s: torch.randn(*s, dtype=torch.bfloat16) * 0.4)(H, Dh, Dm) * (H * Dh) ** (-0.5)), 'seg_len': seg}
    _A_in = _A_setup()

    def _B_setup():
        B, S, D, F = (1, 2048, 1024, 3584)
        return {'x': _w((lambda *s: torch.randn(*s, dtype=torch.bfloat16) * 0.05)(B, S, D)), 'w_gate': _w((lambda *s: torch.randn(*s, dtype=torch.bfloat16) * 0.05)(D, F)), 'w_up': _w((lambda *s: torch.randn(*s, dtype=torch.bfloat16) * 0.05)(D, F)), 'w_down': _w((lambda *s: torch.randn(*s, dtype=torch.bfloat16) * 0.05)(F, D))}
    _B_in = _B_setup()
    return {'A_x': _A_in['x'], 'A_mem0': _A_in['mem0'], 'A_Wq': _A_in['Wq'], 'A_Wk': _A_in['Wk'], 'A_Wv': _A_in['Wv'], 'A_Wo': _A_in['Wo'], 'A_seg_len': _A_in['seg_len'], 'B_x': _B_in['x'], 'B_w_gate': _B_in['w_gate'], 'B_w_up': _B_in['w_up'], 'B_w_down': _B_in['w_down'], 'gate_w': _w((lambda *s: torch.randn(*s, dtype=torch.bfloat16) * 0.05)(1024) * 16.0)}

def reference(A_x, A_mem0, A_Wq, A_Wk, A_Wv, A_Wo, A_seg_len, B_x, B_w_gate, B_w_up, B_w_down, gate_w):

    def _A_ref(x, mem0, Wq, Wk, Wv, Wo, seg_len):
        B, S, Dm = x.shape
        H, Dh = (Wq.shape[1], Wq.shape[2])
        M = mem0.shape[1]
        scale = Dh ** (-0.5)
        n_seg = S // seg_len
        L = M + seg_len
        idx = torch.arange(L)
        mask = (idx[:, None] < M) | (idx[:, None] >= idx[None, :])
        mem = mem0
        outs = []
        for s in range(n_seg):
            xs = x[:, s * seg_len:(s + 1) * seg_len, :].clone()
            h = torch.concatenate([mem, xs], axis=1)
            q = torch.einsum('btd,dhe->bhte', h, Wq)
            k = torch.einsum('btd,dhe->bhte', h, Wk)
            v = torch.einsum('btd,dhe->bhte', h, Wv)
            scores = torch.einsum('bhqe,bhke->bhqk', q, k) * scale
            scores = torch.where(mask[None, None], scores, -1000000000.0)
            p = _softmax(scores, axis=-1)
            o = torch.einsum('bhqk,bhke->bhqe', p, v)
            o = torch.einsum('bhte,hed->btd', o, Wo)
            mem = o[:, :M, :].clone()
            outs.append(o[:, M:, :])
        return torch.concatenate(outs, axis=1)

    def _B_ref(x, w_gate, w_up, w_down):
        g = _silu(x @ w_gate)
        u = x @ w_up
        return g * u @ w_down
    x = A_x
    g = _sigmoid((x * gate_w).sum(-1, keepdims=True))
    a = _A_ref(x, A_mem0, A_Wq, A_Wk, A_Wv, A_Wo, A_seg_len)
    b = _B_ref(x, B_w_gate, B_w_up, B_w_down)
    return g * a + (1 - g) * b
```

```cpp
#include <cuda_runtime.h>
#include <cuda_bf16.h>
#include <cuda.h>
#include <stdint.h>

#define REC_PROF 0

namespace {

constexpr int S_LEN = 2048, DM = 1024, NH = 32, DH = 128, NMEM = 8, SEG = 32, NSEG = 64, FF = 3584;
constexpr int HD = NH * DH;

__device__ __nv_bfloat16 gOx[S_LEN * HD];
__device__ __nv_bfloat16 gHid[S_LEN * FF];
__device__ float gGate[S_LEN];
__device__ uint4 gPart[64 * 32 * 32];
__device__ uint4 gMem[4 * 1024];

__device__ __forceinline__ uint32_t smem_u32(const void* p) { return (uint32_t)__cvta_generic_to_shared(p); }
__device__ __forceinline__ uint32_t mapa(uint32_t a, uint32_t r) {
  uint32_t o; asm volatile("mapa.shared::cluster.u32 %0, %1, %2;" : "=r"(o) : "r"(a), "r"(r)); return o;
}
__device__ __forceinline__ void mbar_init(uint32_t bar, uint32_t cnt) {
  asm volatile("mbarrier.init.shared::cta.b64 [%0], %1;" :: "r"(bar), "r"(cnt) : "memory");
}
__device__ __forceinline__ void mbar_arrive(uint32_t bar) {
  asm volatile("mbarrier.arrive.shared::cta.b64 _, [%0];" :: "r"(bar) : "memory");
}
__device__ __forceinline__ void mbar_expect(uint32_t bar, uint32_t bytes) {
  asm volatile("mbarrier.arrive.expect_tx.shared::cta.b64 _, [%0], %1;" :: "r"(bar), "r"(bytes) : "memory");
}
__device__ __forceinline__ bool mbar_try(uint32_t bar, uint32_t parity) {
  uint32_t ok;
  asm volatile("{\n.reg .pred p;\nmbarrier.try_wait.parity.shared::cta.b64 p, [%1], %2;\nselp.u32 %0, 1, 0, p;\n}"
               : "=r"(ok) : "r"(bar), "r"(parity) : "memory");
  return ok != 0;
}
__device__ __forceinline__ void mbar_wait(uint32_t bar, uint32_t parity, int& budget) {
  while (!mbar_try(bar, parity)) { if (--budget < 0) break; }
}
__device__ __forceinline__ void fence_async() { asm volatile("fence.proxy.async.shared::cta;" ::: "memory"); }
__device__ __forceinline__ void bar_sync(int id, int n) { asm volatile("bar.sync %0, %1;" :: "r"(id), "r"(n) : "memory"); }
__device__ __forceinline__ void bar_arrive(int id, int n) { asm volatile("bar.arrive %0, %1;" :: "r"(id), "r"(n) : "memory"); }

__device__ __forceinline__ void tma_load2d(uint32_t dst, const CUtensorMap* tm, int c0, int c1, uint32_t bar) {
  asm volatile("cp.async.bulk.tensor.2d.shared::cluster.global.mbarrier::complete_tx::bytes [%0], [%1, {%3, %4}], [%2];"
               :: "r"(dst), "l"(tm), "r"(bar), "r"(c0), "r"(c1) : "memory");
}
__device__ __forceinline__ void tma_load3d_mc(uint32_t dst, const CUtensorMap* tm, int c0, int c1, int c2, uint32_t bar, uint16_t mask) {
  asm volatile("cp.async.bulk.tensor.3d.shared::cluster.global.mbarrier::complete_tx::bytes.multicast::cluster [%0], [%1, {%3, %4, %5}], [%2], %6;"
               :: "r"(dst), "l"(tm), "r"(bar), "r"(c0), "r"(c1), "r"(c2), "h"(mask) : "memory");
}
__device__ __forceinline__ void mbar_arrive_remote(uint32_t bar) {
  asm volatile("mbarrier.arrive.shared::cluster.b64 _, [%0];" :: "r"(bar) : "memory");
}
__device__ __forceinline__ uint32_t clk() { uint32_t t; asm volatile("mov.u32 %0, %%clock;" : "=r"(t) :: "memory"); return t; }
__device__ __forceinline__ uint32_t phase_bad(const uint4& v, uint32_t ph) {
  uint32_t a, b;
  asm("lop3.b32 %0, %1, %2, %3, 0x7E;" : "=r"(a) : "r"(v.x), "r"(v.y), "r"(ph));
  asm("lop3.b32 %0, %1, %2, %3, 0x7E;" : "=r"(b) : "r"(v.z), "r"(v.w), "r"(ph));
  return (a | b) & 1u;
}
__device__ __forceinline__ bool has_zero(const uint4& v) { return min(min(v.x, v.y), min(v.z, v.w)) == 0; }
__device__ __forceinline__ uint32_t par(int s) { uint32_t r; asm volatile("and.b32 %0, %1, 1;" : "=r"(r) : "r"(s)); return r; }
__device__ __forceinline__ int otid() { int t; asm volatile("mov.u32 %0, %%tid.x;" : "=r"(t)); return t; }
__device__ __forceinline__ float ex2(float x) { float y; asm("ex2.approx.ftz.f32 %0, %1;" : "=f"(y) : "f"(x)); return y; }
__device__ __forceinline__ float rcp(float x) { float y; asm("rcp.approx.ftz.f32 %0, %1;" : "=f"(y) : "f"(x)); return y; }
__device__ __forceinline__ void tma_store2d(const CUtensorMap* tm, uint32_t src, int c0, int c1) {
  asm volatile("cp.async.bulk.tensor.2d.global.shared::cta.bulk_group [%0, {%2, %3}], [%1];"
               :: "l"(tm), "r"(src), "r"(c0), "r"(c1) : "memory");
}
__device__ __forceinline__ void bulk_commit() { asm volatile("cp.async.bulk.commit_group;" ::: "memory"); }
__device__ __forceinline__ void bulk_wait_read0() { asm volatile("cp.async.bulk.wait_group.read 0;" ::: "memory"); }
__device__ __forceinline__ void bulk_wait0() { asm volatile("cp.async.bulk.wait_group 0;" ::: "memory"); }
__device__ __forceinline__ void bulk_s2c(uint32_t dst, uint32_t src, uint32_t bytes, uint32_t bar) {
  asm volatile("cp.async.bulk.shared::cluster.shared::cta.mbarrier::complete_tx::bytes [%0], [%1], %2, [%3];"
               :: "r"(dst), "r"(src), "r"(bytes), "r"(bar) : "memory");
}
__device__ __forceinline__ void st_async32(uint32_t dst, uint32_t v, uint32_t bar) {
  asm volatile("st.async.shared::cluster.mbarrier::complete_tx::bytes.u32 [%0], %1, [%2];" :: "r"(dst), "r"(v), "r"(bar) : "memory");
}
__device__ __forceinline__ void sts32(uint32_t a, uint32_t v) { asm volatile("st.shared.u32 [%0], %1;" :: "r"(a), "r"(v) : "memory"); }
__device__ __forceinline__ void sts128(uint32_t a, uint4 v) {
  asm volatile("st.shared.v4.u32 [%0], {%1,%2,%3,%4};" :: "r"(a), "r"(v.x), "r"(v.y), "r"(v.z), "r"(v.w) : "memory");
}
__device__ __forceinline__ uint4 ld_relaxed128(const void* p) {
  uint4 v;
  asm volatile("ld.relaxed.gpu.global.v4.u32 {%0,%1,%2,%3}, [%4];" : "=r"(v.x), "=r"(v.y), "=r"(v.z), "=r"(v.w) : "l"(p) : "memory");
  return v;
}
__device__ __forceinline__ void st_relaxed128(void* p, uint32_t a, uint32_t b, uint32_t c, uint32_t d) {
  asm volatile("st.relaxed.gpu.global.v4.u32 [%0], {%1,%2,%3,%4};" :: "l"(p), "r"(a), "r"(b), "r"(c), "r"(d) : "memory");
}
__device__ __forceinline__ void st_relaxed32(void* p, uint32_t a) {
  asm volatile("st.relaxed.gpu.global.u32 [%0], %1;" :: "l"(p), "r"(a) : "memory");
}
__device__ __forceinline__ uint32_t pack_bf16(float lo, float hi) {
  uint32_t r; asm("cvt.rn.bf16x2.f32 %0, %1, %2;" : "=r"(r) : "f"(hi), "f"(lo)); return r;
}
__device__ __forceinline__ void ldsm4_t(uint32_t* r, uint32_t addr) {
  asm volatile("ldmatrix.sync.aligned.m8n8.x4.trans.shared.b16 {%0,%1,%2,%3}, [%4];"
               : "=r"(r[0]), "=r"(r[1]), "=r"(r[2]), "=r"(r[3]) : "r"(addr) : "memory");
}
__device__ __forceinline__ void ldsm4(uint32_t* r, uint32_t addr) {
  asm volatile("ldmatrix.sync.aligned.m8n8.x4.shared.b16 {%0,%1,%2,%3}, [%4];"
               : "=r"(r[0]), "=r"(r[1]), "=r"(r[2]), "=r"(r[3]) : "r"(addr) : "memory");
}
__device__ __forceinline__ void mma16816(float* d, const uint32_t* a, uint32_t b0, uint32_t b1) {
  asm volatile("mma.sync.aligned.m16n8k16.row.col.f32.bf16.bf16.f32 {%0,%1,%2,%3}, {%4,%5,%6,%7}, {%8,%9}, {%0,%1,%2,%3};"
               : "+f"(d[0]), "+f"(d[1]), "+f"(d[2]), "+f"(d[3]) : "r"(a[0]), "r"(a[1]), "r"(a[2]), "r"(a[3]), "r"(b0), "r"(b1));
}
__device__ __forceinline__ void stsm4_t(uint32_t addr, uint32_t a, uint32_t b, uint32_t c, uint32_t d) {
  asm volatile("stmatrix.sync.aligned.m8n8.x4.trans.shared.b16 [%0], {%1,%2,%3,%4};" :: "r"(addr), "r"(a), "r"(b), "r"(c), "r"(d) : "memory");
}
__device__ __forceinline__ void stsm4(uint32_t addr, uint32_t a, uint32_t b, uint32_t c, uint32_t d) {
  asm volatile("stmatrix.sync.aligned.m8n8.x4.shared.b16 [%0], {%1,%2,%3,%4};" :: "r"(addr), "r"(a), "r"(b), "r"(c), "r"(d) : "memory");
}
__device__ __forceinline__ uint32_t movm_t(uint32_t a) {
  uint32_t d; asm volatile("movmatrix.sync.aligned.m8n8.trans.b16 %0, %1;" : "=r"(d) : "r"(a)); return d;
}

struct Desc { uint32_t base, off, hi; };
__device__ __forceinline__ Desc mkd(uint32_t base, uint32_t boff, uint32_t lbo, uint32_t sbo, uint32_t swz) {
  return Desc{base, (boff >> 4) + ((lbo >> 4) << 16), (sbo >> 4) | (swz << 30)};
}
#define WG_FENCE() asm volatile("wgmma.fence.sync.aligned;" ::: "memory")
#define WG_COMMIT() asm volatile("wgmma.commit_group.sync.aligned;" ::: "memory")
#define WG_WAIT(n) asm volatile("wgmma.wait_group.sync.aligned " #n ";" ::: "memory")

#define ZERO(a, n) _Pragma("unroll") for (int _i = 0; _i < n; _i++) a[_i] = 0.f
#define F4(d, o) "+f"(d[o]), "+f"(d[o + 1]), "+f"(d[o + 2]), "+f"(d[o + 3])
#define F16(d, o) F4(d, o), F4(d, o + 4), F4(d, o + 8), F4(d, o + 12)
#define F64(d, o) F16(d, o), F16(d, o + 16), F16(d, o + 32), F16(d, o + 48)

template <int TB> __device__ __forceinline__ void wg_rs8(float* d, const uint32_t* a, Desc b, int sc) {
  asm volatile("{\n.reg .pred p;\n.reg .b32 lb;\n.reg .b64 db;\nsetp.ne.b32 p, %11, 0;\nadd.u32 lb, %8, %9;\nmov.b64 db, {lb, %10};\n"
               "wgmma.mma_async.sync.aligned.m64n8k16.f32.bf16.bf16 {%0,%1,%2,%3}, {%4,%5,%6,%7}, db, p, 1, 1, %12;\n}"
               : F4(d, 0) : "r"(a[0]), "r"(a[1]), "r"(a[2]), "r"(a[3]), "r"(b.base), "r"(b.off), "r"(b.hi), "r"(sc), "n"(TB));
}
template <int TA, int TB> __device__ __forceinline__ void wg_ss8(float* d, Desc a, Desc b, int sc) {
  asm volatile("{\n.reg .pred p;\n.reg .b32 la, lb;\n.reg .b64 da, db;\nsetp.ne.b32 p, %10, 0;\n"
               "add.u32 la, %4, %5;\nmov.b64 da, {la, %6};\nadd.u32 lb, %7, %8;\nmov.b64 db, {lb, %9};\n"
               "wgmma.mma_async.sync.aligned.m64n8k16.f32.bf16.bf16 {%0,%1,%2,%3}, da, db, p, 1, 1, %11, %12;\n}"
               : F4(d, 0) : "r"(a.base), "r"(a.off), "r"(a.hi), "r"(b.base), "r"(b.off), "r"(b.hi), "r"(sc), "n"(TA), "n"(TB));
}
template <int TB> __device__ __forceinline__ void wg_rs32(float* d, const uint32_t* a, Desc b, int sc) {
  asm volatile("{\n.reg .pred p;\n.reg .b32 lb;\n.reg .b64 db;\nsetp.ne.b32 p, %23, 0;\nadd.u32 lb, %20, %21;\nmov.b64 db, {lb, %22};\n"
               "wgmma.mma_async.sync.aligned.m64n32k16.f32.bf16.bf16 {%0,%1,%2,%3,%4,%5,%6,%7,%8,%9,%10,%11,%12,%13,%14,%15}, {%16,%17,%18,%19}, db, p, 1, 1, %24;\n}"
               : F16(d, 0) : "r"(a[0]), "r"(a[1]), "r"(a[2]), "r"(a[3]), "r"(b.base), "r"(b.off), "r"(b.hi), "r"(sc), "n"(TB));
}
template <int TA, int TB> __device__ __forceinline__ void wg_ss32(float* d, Desc a, Desc b, int sc) {
  asm volatile("{\n.reg .pred p;\n.reg .b32 la, lb;\n.reg .b64 da, db;\nsetp.ne.b32 p, %22, 0;\n"
               "add.u32 la, %16, %17;\nmov.b64 da, {la, %18};\nadd.u32 lb, %19, %20;\nmov.b64 db, {lb, %21};\n"
               "wgmma.mma_async.sync.aligned.m64n32k16.f32.bf16.bf16 {%0,%1,%2,%3,%4,%5,%6,%7,%8,%9,%10,%11,%12,%13,%14,%15}, da, db, p, 1, 1, %23, %24;\n}"
               : F16(d, 0) : "r"(a.base), "r"(a.off), "r"(a.hi), "r"(b.base), "r"(b.off), "r"(b.hi), "r"(sc), "n"(TA), "n"(TB));
}
template <int TA, int TB> __device__ __forceinline__ void wg_ss40(float* d, Desc a, Desc b, int sc) {
  asm volatile("{\n.reg .pred p;\n.reg .b32 la, lb;\n.reg .b64 da, db;\nsetp.ne.b32 p, %26, 0;\n"
               "add.u32 la, %20, %21;\nmov.b64 da, {la, %22};\nadd.u32 lb, %23, %24;\nmov.b64 db, {lb, %25};\n"
               "wgmma.mma_async.sync.aligned.m64n40k16.f32.bf16.bf16 {%0,%1,%2,%3,%4,%5,%6,%7,%8,%9,%10,%11,%12,%13,%14,%15,%16,%17,%18,%19}, da, db, p, 1, 1, %27, %28;\n}"
               : F16(d, 0), F4(d, 16) : "r"(a.base), "r"(a.off), "r"(a.hi), "r"(b.base), "r"(b.off), "r"(b.hi), "r"(sc), "n"(TA), "n"(TB));
}
template <int TA, int TB> __device__ __forceinline__ void wg_ss128(float* d, Desc a, Desc b, int sc) {
  asm volatile("{\n.reg .pred p;\n.reg .b32 la, lb;\n.reg .b64 da, db;\nsetp.ne.b32 p, %70, 0;\n"
               "add.u32 la, %64, %65;\nmov.b64 da, {la, %66};\nadd.u32 lb, %67, %68;\nmov.b64 db, {lb, %69};\n"
               "wgmma.mma_async.sync.aligned.m64n128k16.f32.bf16.bf16 {%0,%1,%2,%3,%4,%5,%6,%7,%8,%9,%10,%11,%12,%13,%14,%15,%16,%17,%18,%19,%20,%21,%22,%23,%24,%25,%26,%27,%28,%29,%30,%31,%32,%33,%34,%35,%36,%37,%38,%39,%40,%41,%42,%43,%44,%45,%46,%47,%48,%49,%50,%51,%52,%53,%54,%55,%56,%57,%58,%59,%60,%61,%62,%63}, da, db, p, 1, 1, %71, %72;\n}"
               : F64(d, 0) : "r"(a.base), "r"(a.off), "r"(a.hi), "r"(b.base), "r"(b.off), "r"(b.hi), "r"(sc), "n"(TA), "n"(TB));
}
template <int TA, int TB> __device__ __forceinline__ void wg_ss256(float* d, Desc a, Desc b, int sc) {
  asm volatile("{\n.reg .pred p;\n.reg .b32 la, lb;\n.reg .b64 da, db;\nsetp.ne.b32 p, %134, 0;\n"
               "add.u32 la, %128, %129;\nmov.b64 da, {la, %130};\nadd.u32 lb, %131, %132;\nmov.b64 db, {lb, %133};\n"
               "wgmma.mma_async.sync.aligned.m64n256k16.f32.bf16.bf16 {%0,%1,%2,%3,%4,%5,%6,%7,%8,%9,%10,%11,%12,%13,%14,%15,%16,%17,%18,%19,%20,%21,%22,%23,%24,%25,%26,%27,%28,%29,%30,%31,%32,%33,%34,%35,%36,%37,%38,%39,%40,%41,%42,%43,%44,%45,%46,%47,%48,%49,%50,%51,%52,%53,%54,%55,%56,%57,%58,%59,%60,%61,%62,%63,%64,%65,%66,%67,%68,%69,%70,%71,%72,%73,%74,%75,%76,%77,%78,%79,%80,%81,%82,%83,%84,%85,%86,%87,%88,%89,%90,%91,%92,%93,%94,%95,%96,%97,%98,%99,%100,%101,%102,%103,%104,%105,%106,%107,%108,%109,%110,%111,%112,%113,%114,%115,%116,%117,%118,%119,%120,%121,%122,%123,%124,%125,%126,%127}, da, db, p, 1, 1, %135, %136;\n}"
               : F64(d, 0), F64(d, 64) : "r"(a.base), "r"(a.off), "r"(a.hi), "r"(b.base), "r"(b.off), "r"(b.hi), "r"(sc), "n"(TA), "n"(TB));
}

constexpr int NRS = 44;
constexpr int NRSC = NRS / 4;
constexpr uint32_t R_SS = 0;
constexpr uint32_t R_POOL = 81920;
constexpr uint32_t R_MRS = R_POOL + 25600;
constexpr uint32_t R_P = R_POOL + 32768;
constexpr uint32_t R_V = 118784;
constexpr uint32_t R_K = 129024;
constexpr uint32_t R_Q = 139264;
constexpr uint32_t R_WO = R_Q + 10240;
constexpr uint32_t R_BAR = 231424;
constexpr uint32_t REC_SMEM = 231680;
enum { B_XFULL = 0, B_SSFULL = 6, B_XEMPTY = 8, B_POOL = 16, B_BFREE = 17, B_QKV = 18, B_KVX = 19, B_TFREE = 20, B_WSS = 21, B_WO = 22, B_W0 = 24 };

struct RecMaps { CUtensorMap w[3]; CUtensorMap wo; CUtensorMap wo_half; CUtensorMap x; CUtensorMap x1; CUtensorMap ox; int tune[8]; };

#define PROF(i) do {} while (0)
#define PDUMP() do {} while (0)
#define PVAL(i, v) do {} while (0)
#define DELAY(i) do {} while (0)

__global__ void __cluster_dims__(3, 1, 1) __launch_bounds__(384, 1)
rec_kernel(const __grid_constant__ RecMaps maps, const __nv_bfloat16* __restrict__ mem0) {
  extern __shared__ __align__(1024) uint8_t smem[];
  const uint32_t sb = smem_u32(smem);
  const int tid = threadIdx.x, lane = tid & 31;
  const int wid = __shfl_sync(~0u, tid >> 5, 0), wg = wid >> 2, wp = wid & 3;
  const uint32_t s16 = (sb & 0x3FFFF) >> 4;
  const int h = blockIdx.x / 3, c = blockIdx.x % 3;
  const uint32_t bars = sb + R_BAR;
  auto BAR = [&](int i) { return bars + 8u * i; };
  const uint32_t sWo = sb + R_WO;
  const int col0 = c == 0 ? 0 : (c == 1 ? 320 : 672);
  int budget = 1 << 22;

  if (tid == 0) {
    for (int i = 0; i < 7; i++) mbar_init(BAR(B_XFULL + i), 1);
    for (int i = 0; i < 4; i++) mbar_init(BAR(B_XEMPTY + i), 24);
    mbar_init(BAR(B_POOL), 3); mbar_init(BAR(B_BFREE), 8);
    mbar_init(BAR(B_QKV), 9); mbar_init(BAR(B_KVX), 9); mbar_init(BAR(B_TFREE), 3);
    mbar_init(BAR(B_WSS), 1); mbar_init(BAR(B_WO), 1);
    for (int i = 0; i < 3; i++) mbar_init(BAR(B_W0 + i), 1);
    asm volatile("fence.mbarrier_init.release.cluster;" ::: "memory");
    fence_async();
    const CUtensorMap* tw = &maps.w[c];
    mbar_expect(BAR(B_W0 + 0), 81920); mbar_expect(BAR(B_W0 + 1), 81920); mbar_expect(BAR(B_W0 + 2), 16384);
    for (int i = 0; i < NRSC; i++) {
      uint32_t dst = i < 5 ? sb + R_SS + i * 16384 : (i < 10 ? sWo + (i - 5) * 16384 : sb + R_POOL);
      uint32_t bar = BAR(B_W0 + i / 5);
      tma_load2d(dst, tw, h * 128, i * 64, bar);
      tma_load2d(dst + 8192, tw, h * 128 + 64, i * 64, bar);
    }
  }
  asm volatile("barrier.cluster.arrive.aligned; barrier.cluster.wait.aligned;" ::: "memory");

  { constexpr int ROLE = 0; PROF(15); (void)ROLE; }

  if (wg < 2) {
    asm volatile("setmaxnreg.inc.sync.aligned.u32 224;");
    constexpr int ROLE = 0; (void)ROLE;
    uint32_t wa[NRS * 4];
#pragma unroll
    for (int i = 0; i < NRSC; i++) {
      if (i % 5 == 0) mbar_wait(BAR(B_W0 + i / 5), 0, budget);
      uint32_t src = (i < 5 ? sb + R_SS + i * 16384 : (i < 10 ? sWo + (i - 5) * 16384 : sb + R_POOL)) + wg * 8192;
#pragma unroll
      for (int j = 0; j < 4; j++) {
        int k = j * 16 + (lane >> 4) * 8 + (lane & 7);
        int mg = wp * 2 + ((lane >> 3) & 1);
        ldsm4_t(&wa[(i * 4 + j) * 4], src + k * 128 + ((mg ^ (k & 7)) << 4));
      }
      if (i == 4 || i == 9 || i == 10) {
        bar_sync(3, 256);
        if (tid == 0) {
          fence_async();
          if (i == 4) {
            mbar_expect(BAR(B_WSS), 81920);
            for (int t = 0; t < 2; t++)
              for (int j = 0; j < 5; j++)
                tma_load2d(sb + R_SS + t * 40960 + j * 8192, &maps.w[c], h * 128 + t * 64, (NRSC + j) * 64, BAR(B_WSS));
          } else if (i == 9) {
            mbar_expect(BAR(B_WO), c == 0 ? 81920 : 90112);
            for (int t = 0; t < 5; t++) tma_load2d(sWo + t * 16384, &maps.wo, col0 + t * 64, h * 128, BAR(B_WO));
            if (c != 0) {
              tma_load2d(sb + R_Q + 1024, &maps.wo_half, col0 + 320, h * 128, BAR(B_WO));
              tma_load2d(sb + R_Q + 6144, &maps.wo_half, col0 + 320, h * 128 + 64, BAR(B_WO));
            }
          } else {
            mbar_arrive_remote(mapa(BAR(B_POOL), 0));
          }
        }
      }
    }
    mbar_wait(BAR(B_WSS), 0, budget);
    const uint32_t aSS = s16 + (R_SS >> 4) + wg * 2560;
    const uint32_t aWo = s16 + (R_WO >> 4) + wg * 1024;
    const uint32_t tbase = (c == 0 ? R_Q : (c == 1 ? R_K : R_V));
    PROF(0);

#pragma unroll 1
    for (int s = -1; s < NSEG; s++) {
      float mr[4];
      ZERO(mr, 4);
      if (tid < 7 && s + 1 < NSEG) mbar_expect(BAR(B_XFULL + tid), tid == 6 ? 20480 : 8192);
      if (s >= 0) {
        bar_sync(1, 384);
        PROF(1);
        float am[12];
        ZERO(am, 12);
        const int ln = otid() & 31;
        const uint32_t ma = sb + R_MRS + (ln & 7) * 128;
        const uint32_t x0 = ((ln >> 3) ^ (ln & 7)) << 4;
        uint32_t bf[2][4];
        ldsm4(bf[0], ma + x0);
#pragma unroll
        for (int j = 0; j < NRS / 2; j++) {
          if (j + 1 < NRS / 2) ldsm4(bf[(j + 1) & 1], ma + ((j + 1) >> 1) * 1024 + (x0 ^ (((j + 1) & 1) << 6)));
          mma16816((j & 1) ? am + 4 : mr, &wa[j * 8], bf[j & 1][0], bf[j & 1][1]);
          mma16816((j & 1) ? am + 8 : am, &wa[j * 8 + 4], bf[j & 1][2], bf[j & 1][3]);
        }
#pragma unroll
        for (int e = 0; e < 4; e++) mr[e] = (mr[e] + am[e]) + (am[4 + e] + am[8 + e]);
        PROF(8);
      }
      if (s + 1 < NSEG) mbar_wait(BAR(B_SSFULL), (s + 1) & 1, budget);
      float a40[20];
      ZERO(a40, 16);
#pragma unroll
      for (int e = 0; e < 4; e++) a40[16 + e] = mr[e];
      WG_FENCE();
#pragma unroll
      for (int j = 0; j < 20; j++)
        wg_ss40<1, 0>(a40, mkd(aSS, j * 2048, 0, 1024, 1), mkd(s16, R_POOL + (j >> 2) * 5120 + (j & 3) * 32, 0, 1024, 1), 1);
      WG_COMMIT();
      WG_WAIT(0);
      float ax[16];
#pragma unroll
      for (int e = 0; e < 16; e++) ax[e] = a40[e];
      if (s < 0) {
        if (lane == 0) mbar_arrive_remote(mapa(BAR(B_XEMPTY + 3), 0));
      } else {
        PROF(2);
        uint32_t m0 = movm_t(pack_bf16(a40[16], a40[17]));
        uint32_t m1 = movm_t(pack_bf16(a40[18], a40[19]));
        {
          const int ln = otid() & 31, tok = ln >> 2;
          const uint32_t o0 = sb + tbase + wg * 5120 + tok * 128 + (((wp * 2) ^ tok) << 4) + (ln & 3) * 4;
#pragma unroll
          for (int r = 1; r < 3; r++) {
            uint32_t rr = c + r >= 3 ? c + r - 3 : c + r;
            uint32_t dst = mapa(o0, rr), rb = mapa(BAR(B_QKV), rr);
            st_async32(dst, m0, rb);
            st_async32(dst ^ 16, m1, rb);
          }
          sts32(o0, m0);
          sts32(o0 ^ 16, m1);
          fence_async();
          __syncwarp();
          if (ln == 0) mbar_arrive(BAR(B_QKV));
        }
        if (s == NSEG - 1) break;
        if (s == 0) mbar_wait(BAR(B_WO), 0, budget);
        PROF(3);
        PDUMP();
        bar_sync(2, 384);
        PROF(4);
        const uint32_t ph = (s + 1) & 1;
        float ao[4];
        ZERO(ao, 4);
#pragma unroll
        for (int t = 0; t < 3; t++) {
          const int tile = t * 2 + wg;
          WG_FENCE();
#pragma unroll
          for (int j = 0; j < 8; j++) {
            Desc db = mkd(s16, R_Q + (j >> 2) * 5120 + (j & 3) * 256, 128, 128, 0);
            Desc da = mkd(aWo, t * 32768 + j * 2048, 0, 1024, 1);
            if (t == 2 && tile == 5) da = mkd(s16, R_Q + 1024 + (j >> 2) * 5120 + (j & 3) * 1024, 0, 512, 2);
            wg_ss8<1, 1>(ao, da, db, j > 0);
          }
          WG_COMMIT();
          WG_WAIT(0);
          if (tile < 5 || (c != 0 && wp < 2)) {
            const int ln = otid() & 31;
            const int cg = ((col0 + tile * 64) >> 4) + wp;
            st_relaxed128(&gPart[(cg * 32 + h) * 32 + (ln & 3) * 8 + (ln >> 2)],
                          (__float_as_uint(ao[0]) & ~1u) | ph, (__float_as_uint(ao[1]) & ~1u) | ph,
                          (__float_as_uint(ao[2]) & ~1u) | ph, (__float_as_uint(ao[3]) & ~1u) | ph);
          }
        }
        bar_arrive(7, 384);
        PROF(5);
        DELAY(3);
      }
#pragma unroll
      for (int i = 0; i < 6; i++) {
        mbar_wait(BAR(B_XFULL + i), (s + 1) & 1, budget);
        WG_FENCE();
#pragma unroll
        for (int j = 0; j < 8; j++) {
          const int ks = i * 8 + j;
          if (ks < NRS) wg_rs32<0>(ax, &wa[ks * 4], mkd(s16, R_POOL + (i & 3) * 8192 + (j >> 2) * 4096 + (j & 3) * 32, 0, 1024, 1), 1);
        }
        WG_COMMIT();
        if (i == 1 || i == 2) {
          WG_WAIT(1);
          if (lane == 0) mbar_arrive_remote(mapa(BAR(B_XEMPTY + (i - 1)), 0));
        }
      }
      WG_WAIT(0);
      if (lane == 0) { mbar_arrive_remote(mapa(BAR(B_XEMPTY + 2), 0)); mbar_arrive(BAR(B_BFREE)); }
      PROF(6);
      if (s >= 0) mbar_wait(BAR(B_TFREE), s & 1, budget);
      {
        uint32_t tb = sb + tbase + wg * 5120;
        const int ln = otid() & 31;
        int r = ln & 7, blk = ln >> 3;
#pragma unroll
        for (int jj = 0; jj < 2; jj++) {
          int tok = 8 + (jj * 2 + (blk >> 1)) * 8 + r;
          int g = wp * 2 + (blk & 1);
          stsm4_t(tb + tok * 128 + ((g ^ r) << 4),
                  pack_bf16(ax[jj * 8 + 0], ax[jj * 8 + 1]), pack_bf16(ax[jj * 8 + 2], ax[jj * 8 + 3]),
                  pack_bf16(ax[jj * 8 + 4], ax[jj * 8 + 5]), pack_bf16(ax[jj * 8 + 6], ax[jj * 8 + 7]));
        }
        fence_async();
        if (c != 0) {
          bar_sync(4 + wg, 128);
          if ((tid & 127) < 2) {
            uint32_t r2 = (tid & 1) == 0 ? 0u : (uint32_t)(3 - c);
            bulk_s2c(mapa(tb + 1024, r2), tb + 1024, 4096, mapa(BAR(B_KVX), r2));
          }
        }
        __syncwarp();
        if (lane == 0) mbar_arrive(BAR(B_KVX));
      }
      PROF(7);
    }
  } else {
    asm volatile("setmaxnreg.dec.sync.aligned.u32 56;");
    constexpr int ROLE = 1; (void)ROLE;
    const float sl2e = 0.08838834764831845f * 1.4426950408889634f;
    if (tid == 256) {
      mbar_expect(BAR(B_QKV), 4096);
      mbar_expect(BAR(B_KVX), c == 0 ? 16384 : 8192);
    }
    if (c == 0 && tid == 352) {
      mbar_wait(BAR(B_POOL), 0, budget);
      for (int j = 0; j < 5; j++) tma_load3d_mc(sb + R_POOL + j * 5120, &maps.x1, 0, 0, NRSC + j, BAR(B_SSFULL), 7);
      mbar_wait(BAR(B_XEMPTY + 3), 0, budget);
      for (int j = 0; j < 4; j++) tma_load3d_mc(sb + R_POOL + j * 8192, &maps.x, 0, 0, j * 2, BAR(B_XFULL + j), 7);
      for (int j = 0; j < 2; j++) {
        mbar_wait(BAR(B_XEMPTY + j), 0, budget);
        tma_load3d_mc(sb + R_POOL + j * 8192, &maps.x, 0, 0, 8 + j * 2, BAR(B_XFULL + 4 + j), 7);
      }
      mbar_wait(BAR(B_XEMPTY + 2), 0, budget);
      for (int j = 0; j < 5; j++) tma_load3d_mc(sb + R_POOL + j * 5120, &maps.x1, 0, SEG, NRSC + j, BAR(B_SSFULL), 7);
    }
    __syncwarp();
    mbar_wait(BAR(B_BFREE), 0, budget);
#pragma unroll 1
    for (int i = 0; i < 8; i++) {
      const int u = i * 128 + (tid - 256), ch = u >> 6, n = (u >> 3) & 7, g = u & 7;
      const uint4 v = *reinterpret_cast<const uint4*>(mem0 + n * DM + ch * 64 + g * 8);
      sts128(sb + (ch < NRSC ? R_MRS + ch * 1024 : R_POOL + (ch - NRSC) * 5120 + 4096) + n * 128 + ((g ^ n) << 4), v);
    }
#pragma unroll 1
    for (int s = 0; s < NSEG; s++) {
      fence_async();
      bar_arrive(1, 384);
      PROF(2);
      PDUMP();
      mbar_wait(BAR(B_KVX), par(s), budget);
      mbar_wait(BAR(B_QKV), par(s), budget);
      PROF(3);
      fence_async();
      float sc[20];
      ZERO(sc, 20);
      WG_FENCE();
#pragma unroll
      for (int j = 0; j < 8; j++) {
        Desc da = mkd(s16, R_Q + (j >> 2) * 5120 + (j & 3) * 32, 0, 1024, 1);
        Desc db = mkd(s16, R_K + (j >> 2) * 5120 + (j & 3) * 32, 0, 1024, 1);
        wg_ss40<0, 0>(sc, da, db, j > 0);
      }
      WG_COMMIT();
      WG_WAIT(0);
      PROF(4);
      const bool more = s + 1 < NSEG;
      if (more) {
        if (wp == 0) {
          float mx = fmaxf(fmaxf(fmaxf(sc[0], sc[1]), fmaxf(sc[4], sc[5])), fmaxf(fmaxf(sc[8], sc[9]), fmaxf(sc[12], sc[13])));
          mx = fmaxf(mx, fmaxf(sc[16], sc[17]));
          mx = fmaxf(mx, __shfl_xor_sync(~0u, mx, 1));
          mx = fmaxf(mx, __shfl_xor_sync(~0u, mx, 2));
          const float mo = -mx * sl2e;
          float p[10];
#pragma unroll
          for (int j = 0; j < 5; j++) { p[2 * j] = ex2(fmaf(sc[4 * j], sl2e, mo)); p[2 * j + 1] = ex2(fmaf(sc[4 * j + 1], sl2e, mo)); }
          float sum = (((p[0] + p[1]) + (p[2] + p[3])) + ((p[4] + p[5]) + (p[6] + p[7]))) + (p[8] + p[9]);
          sum += __shfl_xor_sync(~0u, sum, 1);
          sum += __shfl_xor_sync(~0u, sum, 2);
          const float inv = rcp(sum);
          const uint32_t pa = sb + R_P + (otid() & 31) * 4;
#pragma unroll
          for (int j = 0; j < 5; j++) sts32(pa + j * 128, pack_bf16(p[2 * j] * inv, p[2 * j + 1] * inv));
          sts32(pa + 640, 0);
          PROF(10);
          fence_async();
        } else if (tid == 352) {
          mbar_expect(BAR(B_QKV), 4096);
          mbar_expect(BAR(B_KVX), c == 0 ? 16384 : 8192);
          if (c == 0)
            for (int j = 0; j < 4; j++) tma_load3d_mc(sb + R_POOL + j * 8192, &maps.x, 0, (s + 1) * SEG, j * 2, BAR(B_XFULL + j), 7);
        }
        __syncwarp();
        bar_sync(6, 128);
        PROF(5);
        float om[8];
        ZERO(om, 8);
        WG_FENCE();
#pragma unroll
        for (int tl = 0; tl < 2; tl++)
#pragma unroll
          for (int j = 0; j < 3; j++)
            wg_ss8<1, 0>(om + tl * 4, mkd(s16, R_V + tl * 5120 + j * 2048, 0, 1024, 1), mkd(s16, R_P + j * 256, 128, 768, 0), j > 0);
        WG_COMMIT();
        WG_WAIT(0);
        const uint32_t ob = sb + R_Q + wp * 256 + (otid() & 31) * 4;
#pragma unroll
        for (int tl = 0; tl < 2; tl++) {
          sts32(ob + tl * 5120, pack_bf16(om[tl * 4], om[tl * 4 + 1]));
          sts32(ob + tl * 5120 + 128, pack_bf16(om[tl * 4 + 2], om[tl * 4 + 3]));
        }
        fence_async();
        bar_arrive(2, 384);
      }
      PROF(6);
      if (c == 0) {
        if (wp < 3) {
          const int ln = otid() & 31;
#pragma unroll
          for (int hf = 0; hf < 2; hf++) {
            const int g = wp * 2 + hf;
            if (g >= 1 && g < 5) {
              const int lim = g * 8 + (ln >> 2) - (ln & 3) * 2;
              float v[10];
#pragma unroll
              for (int j = 0; j < 5; j++) {
                v[2 * j] = (j * 8 <= lim) ? sc[j * 4 + hf * 2] * sl2e : -1.4426950408889634e9f;
                v[2 * j + 1] = (j * 8 + 1 <= lim) ? sc[j * 4 + hf * 2 + 1] * sl2e : -1.4426950408889634e9f;
              }
              float mx = fmaxf(fmaxf(fmaxf(v[0], v[1]), fmaxf(v[2], v[3])), fmaxf(fmaxf(v[4], v[5]), fmaxf(v[6], v[7])));
              mx = fmaxf(mx, fmaxf(v[8], v[9]));
              mx = fmaxf(mx, __shfl_xor_sync(~0u, mx, 1));
              mx = fmaxf(mx, __shfl_xor_sync(~0u, mx, 2));
#pragma unroll
              for (int j = 0; j < 10; j++) v[j] = ex2(v[j] - mx);
              float sum = (((v[0] + v[1]) + (v[2] + v[3])) + ((v[4] + v[5]) + (v[6] + v[7]))) + (v[8] + v[9]);
              sum += __shfl_xor_sync(~0u, sum, 1);
              sum += __shfl_xor_sync(~0u, sum, 2);
              const float inv = rcp(sum);
              const uint32_t pa = sb + R_P + hf * 768 + ((otid() >> 5) & 3) * 1536 + ln * 4;
#pragma unroll
              for (int j = 0; j < 5; j++) sts32(pa + j * 128, pack_bf16(v[2 * j] * inv, v[2 * j + 1] * inv));
              sts32(pa + 640, 0);
            }
          }
          fence_async();
        }
        if (tid == 352 && more) {
          for (int j = 0; j < 2; j++) {
            mbar_wait(BAR(B_XEMPTY + j), par(s + 1), budget);
            tma_load3d_mc(sb + R_POOL + j * 8192, &maps.x, 0, (s + 1) * SEG, 8 + j * 2, BAR(B_XFULL + 4 + j), 7);
          }
        }
        __syncwarp();
        if (more) bar_sync(7, 384); else bar_sync(6, 128);
        PROF(12);
        const int ln = otid() & 31, r = ln & 7, blk = ln >> 3;
        const uint32_t oa = sb + R_Q + (8 + (blk >> 1) * 8 + r) * 128 + (((wp * 2 + (blk & 1)) ^ r) << 4);
#pragma unroll
        for (int tl = 0; tl < 2; tl++) {
          float ox[16];
          ZERO(ox, 16);
          WG_FENCE();
#pragma unroll
          for (int j = 0; j < 3; j++)
            wg_ss32<1, 0>(ox, mkd(s16, R_V + tl * 5120 + j * 2048, 0, 1024, 1), mkd(s16, R_P + 768 + j * 256, 128, 768, 0), j > 0);
          WG_COMMIT();
          WG_WAIT(0);
#pragma unroll
          for (int jj = 0; jj < 2; jj++) {
            const float* a = ox + jj * 8;
            stsm4_t(oa + tl * 5120 + jj * 2048, pack_bf16(a[0], a[1]), pack_bf16(a[2], a[3]), pack_bf16(a[4], a[5]), pack_bf16(a[6], a[7]));
          }
        }
        fence_async();
        bar_sync(6, 128);
        if (tid == 256) {
          tma_store2d(&maps.ox, sb + R_Q + 1024, h * 128, s * SEG);
          tma_store2d(&maps.ox, sb + R_Q + 5120 + 1024, h * 128 + 64, s * SEG);
          bulk_commit();
          bulk_wait_read0();
        }
        if (!more) break;
        __syncwarp();
        { int t = otid() - 256; if (t < 3) mbar_arrive_remote(mapa(BAR(B_TFREE), t)); }
        PROF(7);
        if (tid == 352) {
          if (s + 2 < NSEG) {
            mbar_wait(BAR(B_XEMPTY + 2), par(s + 1), budget);
            for (int j = 0; j < 5; j++) tma_load3d_mc(sb + R_POOL + j * 5120, &maps.x1, 0, (s + 2) * SEG, NRSC + j, BAR(B_SSFULL), 7);
          }
        }
        __syncwarp();
        DELAY(2);
      } else {
        if (!more) break;
        bar_sync(7, 384);
        PROF(12);
        { int t = otid() - 256; if (t < 3) mbar_arrive_remote(mapa(BAR(B_TFREE), t)); }
        DELAY(0);
        budget = __reduce_min_sync(~0u, budget);
        PVAL(11, budget);
        int cg = h * 2 + (c - 1);
        asm volatile("" : "+r"(cg));
        const uint32_t ph = par(s + 1);
        uint4 v[8];
        {
          const int ln = otid() & 31;
          const uint4* src = gPart + (cg * 32 + (ln >> 3)) * 32 + wp * 8 + (ln & 7);
#pragma unroll
          for (int i = 0; i < 8; i++) v[i] = ld_relaxed128(src + i * 128);
          while (true) {
            bool any = false;
#pragma unroll
            for (int i = 0; i < 8; i++) {
              if (phase_bad(v[i], ph)) { any = true; v[i] = ld_relaxed128(src + i * 128); }
            }
            if (!any || --budget < 0) break;
          }
        }
        __syncwarp();
        PROF(8);
        PVAL(13, budget);
        float a[4];
#define RSUM(f) (((__uint_as_float(v[0].f) + __uint_as_float(v[1].f)) + (__uint_as_float(v[2].f) + __uint_as_float(v[3].f))) + \
                 ((__uint_as_float(v[4].f) + __uint_as_float(v[5].f)) + (__uint_as_float(v[6].f) + __uint_as_float(v[7].f))))
        a[0] = RSUM(x); a[1] = RSUM(y); a[2] = RSUM(z); a[3] = RSUM(w);
#undef RSUM
        const int ln = otid() & 31;
        {
          const bool hi = (ln & 8) != 0;
          float k0 = hi ? a[2] : a[0], k1 = hi ? a[3] : a[1], s0 = hi ? a[0] : a[2], s1 = hi ? a[1] : a[3];
          k0 += __shfl_xor_sync(~0u, s0, 8); k1 += __shfl_xor_sync(~0u, s1, 8);
          k0 += __shfl_xor_sync(~0u, k0, 16); k1 += __shfl_xor_sync(~0u, k1, 16);
          const bool odd = (ln & 1) != 0;
          const float rv = __shfl_xor_sync(~0u, odd ? k0 : k1, 1);
          uint32_t w = odd ? pack_bf16(rv, k1) : pack_bf16(k0, rv);
          if (w == 0) w = 0x80000000u;
          const int n = wp * 2 + (ln & 1), kg = (cg & 3) * 2 + ((ln >> 3) & 1);
          const int off = (cg >> 2) * 256 + n * 32 + ((kg ^ n) << 2) + ((ln & 7) >> 1);
          st_relaxed32(reinterpret_cast<uint32_t*>(gMem) + ((s + 1 + (ln >> 4) * 2) & 3) * 4096 + off, ln < 16 ? w : 0u);
        }
        PROF(9);
        DELAY(1);
      }
      {
        budget = __reduce_min_sync(~0u, budget);
        PVAL(0, budget);
        const int t = otid() - 256;
        const uint4* src = gMem + ((s + 1) & 3) * 1024 + t;
        uint4 v[8];
#pragma unroll
        for (int i = 0; i < 8; i++) v[i] = ld_relaxed128(src + i * 128);
        while (true) {
          bool any = false;
#pragma unroll
          for (int i = 0; i < 8; i++) {
            if (has_zero(v[i])) { any = true; v[i] = ld_relaxed128(src + i * 128); }
          }
          if (!any || --budget < 0) break;
        }
        __syncwarp();
        PROF(1);
        PVAL(14, budget);
        mbar_wait(BAR(B_BFREE), par(s + 1), budget);
        const uint32_t d0 = sb + (t & 63) * 16, up = t >> 6;
#pragma unroll
        for (int i = 0; i < 8; i++) {
          uint32_t d;
          if (i < 5) d = R_MRS + i * 2048 + up * 1024;
          else if (i == 5) d = up ? R_POOL + 4096 : R_MRS + 10240;
          else d = R_POOL + (2 * i - NRSC) * 5120 + 4096 + up * 5120;
          sts128(d0 + d, v[i]);
        }
      }
    }
    if (tid == 256) bulk_wait0();
  }
  asm volatile("barrier.cluster.arrive.aligned; barrier.cluster.wait.aligned;" ::: "memory");
}

constexpr int G_STAGES = 4;
constexpr uint32_t G_STAGE1 = 16384 + 32768;

struct GemmMaps { CUtensorMap a0, a1, b0, b1, out; };

__global__ void __launch_bounds__(384, 1)
ffn1_kernel(const __grid_constant__ GemmMaps maps, const __nv_bfloat16* __restrict__ x, const __nv_bfloat16* __restrict__ gw) {
  extern __shared__ __align__(1024) uint8_t smem[];
  const uint32_t sb = smem_u32(smem);
  const uint32_t sOut = sb + G_STAGES * G_STAGE1;
  const uint32_t bars = sOut + 32768;
  const int tid = threadIdx.x, lane = tid & 31;
  const int wid = __shfl_sync(~0u, tid >> 5, 0), wg = wid >> 2, wp = wid & 3;
  constexpr int NT = 16 * 28;
  int budget = 1 << 22;
  if (tid == 0) {
    for (int i = 0; i < G_STAGES; i++) { mbar_init(bars + 8 * i, 1); mbar_init(bars + 64 + 8 * i, 8); }
    fence_async();
  }
  __syncthreads();
  if (wg == 2) {
    asm volatile("setmaxnreg.dec.sync.aligned.u32 40;");
    if (wp == 0) {
      if (lane == 0) {
        int it = 0;
        for (int tile = blockIdx.x; tile < NT; tile += gridDim.x) {
          int mb = tile & 15, nb = tile >> 4;
          for (int k = 0; k < 16; k++, it++) {
            int st = it % G_STAGES;
            mbar_wait(bars + 64 + 8 * st, ((it / G_STAGES) & 1) ^ 1, budget);
            uint32_t d = sb + st * G_STAGE1, fb = bars + 8 * st;
            mbar_expect(fb, G_STAGE1);
            tma_load2d(d, &maps.a0, k * 64, mb * 128, fb);
            tma_load2d(d + 16384, &maps.b0, nb * 128, k * 64, fb);
            tma_load2d(d + 24576, &maps.b0, nb * 128 + 64, k * 64, fb);
            tma_load2d(d + 32768, &maps.b1, nb * 128, k * 64, fb);
            tma_load2d(d + 40960, &maps.b1, nb * 128 + 64, k * 64, fb);
          }
        }
      }
    } else {
      for (int row = blockIdx.x * 3 + (wp - 1); row < S_LEN; row += gridDim.x * 3) {
        float acc = 0.f;
#pragma unroll 1
        for (int i = 0; i < 4; i++) {
          uint4 a = *reinterpret_cast<const uint4*>(x + row * DM + i * 256 + lane * 8);
          uint4 b = *reinterpret_cast<const uint4*>(gw + i * 256 + lane * 8);
          const uint32_t aa[4] = {a.x, a.y, a.z, a.w}, bb[4] = {b.x, b.y, b.z, b.w};
#pragma unroll
          for (int e = 0; e < 4; e++) {
            acc += __uint_as_float(aa[e] << 16) * __uint_as_float(bb[e] << 16);
            acc += __uint_as_float(aa[e] & 0xFFFF0000u) * __uint_as_float(bb[e] & 0xFFFF0000u);
          }
        }
#pragma unroll
        for (int o = 16; o > 0; o >>= 1) acc += __shfl_xor_sync(~0u, acc, o);
        if (lane == 0) gGate[row] = 1.0f / (1.0f + __expf(-acc));
      }
    }
  } else {
    asm volatile("setmaxnreg.inc.sync.aligned.u32 232;");
    int it = 0;
    for (int tile = blockIdx.x; tile < NT; tile += gridDim.x) {
      int mb = tile & 15, nb = tile >> 4;
      float acc[128];
      for (int k = 0; k < 16; k++, it++) {
        int st = it % G_STAGES;
        mbar_wait(bars + 8 * st, (it / G_STAGES) & 1, budget);
        uint32_t d = sb + st * G_STAGE1;
        uint32_t da = ((d & 0x3FFFF) >> 4) + wg * 512, db = ((d & 0x3FFFF) >> 4) + 1024;
        WG_FENCE();
#pragma unroll
        for (int j = 0; j < 4; j++) wg_ss256<0, 1>(acc, mkd(da, j * 32, 0, 1024, 1), mkd(db, j * 2048, 8192, 1024, 1), (k | j) != 0);
        WG_COMMIT();
        if (k > 0) { WG_WAIT(1); if (lane == 0) mbar_arrive(bars + 64 + 8 * ((it - 1) % G_STAGES)); }
      }
      WG_WAIT(0);
      if (lane == 0) mbar_arrive(bars + 64 + 8 * ((it - 1) % G_STAGES));
      if ((tid & 127) == 0) bulk_wait_read0();
      bar_sync(1 + wg, 128);
      {
        int r = wg * 64 + wp * 16 + (lane & 7) + ((lane >> 3) & 1) * 8;
#pragma unroll
        for (int j = 0; j < 8; j++) {
          uint32_t v[4];
#pragma unroll
          for (int q = 0; q < 4; q++) {
            float g0 = acc[j * 8 + q * 2], g1 = acc[j * 8 + q * 2 + 1];
            float u0 = acc[64 + j * 8 + q * 2], u1 = acc[64 + j * 8 + q * 2 + 1];
            v[q] = pack_bf16(g0 / (1.0f + __expf(-g0)) * u0, g1 / (1.0f + __expf(-g1)) * u1);
          }
          int g = (j & 3) * 2 + (lane >> 4);
          stsm4(sOut + (j >> 2) * 16384 + r * 128 + ((g ^ (r & 7)) << 4), v[0], v[1], v[2], v[3]);
        }
      }
      fence_async();
      bar_sync(1 + wg, 128);
      if ((tid & 127) == 0) {
        tma_store2d(&maps.out, sOut + wg * 8192, nb * 128, mb * 128 + wg * 64);
        tma_store2d(&maps.out, sOut + 16384 + wg * 8192, nb * 128 + 64, mb * 128 + wg * 64);
        bulk_commit();
      }
    }
    if ((tid & 127) == 0) bulk_wait0();
  }
}

constexpr int F_STAGES = 6;
constexpr uint32_t F_STAGE = 32768;

__global__ void __launch_bounds__(384, 1)
fin_kernel(const __grid_constant__ GemmMaps maps) {
  extern __shared__ __align__(1024) uint8_t smem[];
  const uint32_t sb = smem_u32(smem);
  const uint32_t sOut = sb + F_STAGES * F_STAGE;
  const uint32_t bars = sOut + 32768;
  const int tid = threadIdx.x, lane = tid & 31;
  const int wid = __shfl_sync(~0u, tid >> 5, 0), wg = wid >> 2, wp = wid & 3;
  const int mb = blockIdx.x >> 3, nb = blockIdx.x & 7;
  constexpr int KA = HD / 64, KB = FF / 64;
  int budget = 1 << 22;
  if (tid == 0) {
    for (int i = 0; i < F_STAGES; i++) { mbar_init(bars + 8 * i, 1); mbar_init(bars + 64 + 8 * i, 8); }
    fence_async();
  }
  __syncthreads();
  if (wg == 2) {
    asm volatile("setmaxnreg.dec.sync.aligned.u32 40;");
    if (wp == 0) {
      if (lane == 0) {
        for (int it = 0; it < KA + KB; it++) {
          int st = it % F_STAGES;
          mbar_wait(bars + 64 + 8 * st, ((it / F_STAGES) & 1) ^ 1, budget);
          uint32_t d = sb + st * F_STAGE, fb = bars + 8 * st;
          mbar_expect(fb, F_STAGE);
          const CUtensorMap* ta = it < KA ? &maps.a0 : &maps.a1;
          const CUtensorMap* tb = it < KA ? &maps.b0 : &maps.b1;
          int k = (it < KA ? it : it - KA) * 64;
          tma_load2d(d, ta, k, mb * 128, fb);
          tma_load2d(d + 16384, tb, nb * 128, k, fb);
          tma_load2d(d + 24576, tb, nb * 128 + 64, k, fb);
        }
      }
    } else {
      for (int i = blockIdx.x * 96 + (tid - 288); i < 64 * 32 * 32; i += gridDim.x * 96) gPart[i] = make_uint4(0, 0, 0, 0);
      for (int i = blockIdx.x * 96 + (tid - 288); i < 4 * 1024; i += gridDim.x * 96) gMem[i] = make_uint4(0, 0, 0, 0);
    }
  } else {
    asm volatile("setmaxnreg.inc.sync.aligned.u32 232;");
    float acc[64], accb[64];
    for (int it = 0; it < KA + KB; it++) {
      int st = it % F_STAGES;
      mbar_wait(bars + 8 * st, (it / F_STAGES) & 1, budget);
      uint32_t d = sb + st * F_STAGE;
      uint32_t da = ((d & 0x3FFFF) >> 4) + wg * 512, db = ((d & 0x3FFFF) >> 4) + 1024;
      WG_FENCE();
      if (it < KA) {
#pragma unroll
        for (int j = 0; j < 4; j++) wg_ss128<0, 1>(acc, mkd(da, j * 32, 0, 1024, 1), mkd(db, j * 2048, 8192, 1024, 1), (it | j) != 0);
      } else {
#pragma unroll
        for (int j = 0; j < 4; j++) wg_ss128<0, 1>(accb, mkd(da, j * 32, 0, 1024, 1), mkd(db, j * 2048, 8192, 1024, 1), ((it - KA) | j) != 0);
      }
      WG_COMMIT();
      if (it > 0) { WG_WAIT(1); if (lane == 0) mbar_arrive(bars + 64 + 8 * ((it - 1) % F_STAGES)); }
    }
    WG_WAIT(0);
    int row = mb * 128 + wg * 64 + wp * 16 + (lane >> 2);
    float g0 = gGate[row], g1 = gGate[row + 8];
    int r = wg * 64 + wp * 16 + (lane & 7) + ((lane >> 3) & 1) * 8;
#pragma unroll
    for (int j = 0; j < 8; j++) {
      uint32_t v[4];
#pragma unroll
      for (int q = 0; q < 4; q++) {
        float g = (q & 1) ? g1 : g0;
        int i = j * 8 + q * 2;
        v[q] = pack_bf16(g * acc[i] + (1.0f - g) * accb[i], g * acc[i + 1] + (1.0f - g) * accb[i + 1]);
      }
      int g = (j & 3) * 2 + (lane >> 4);
      stsm4(sOut + (j >> 2) * 16384 + r * 128 + ((g ^ (r & 7)) << 4), v[0], v[1], v[2], v[3]);
    }
    fence_async();
    bar_sync(1 + wg, 128);
    if ((tid & 127) == 0) {
      tma_store2d(&maps.out, sOut + wg * 8192, nb * 128, mb * 128 + wg * 64);
      tma_store2d(&maps.out, sOut + 16384 + wg * 8192, nb * 128 + 64, mb * 128 + wg * 64);
      bulk_commit();
      bulk_wait0();
    }
  }
}

typedef CUresult (*EncodeFn)(CUtensorMap*, CUtensorMapDataType, cuuint32_t, void*, const cuuint64_t*, const cuuint64_t*,
                             const cuuint32_t*, const cuuint32_t*, CUtensorMapInterleave, CUtensorMapSwizzle,
                             CUtensorMapL2promotion, CUtensorMapFloatOOBfill);

void make_map(EncodeFn fn, CUtensorMap* m, const void* ptr, uint64_t inner, uint64_t outer, uint32_t bi, uint32_t bo,
              CUtensorMapSwizzle swz) {
  cuuint64_t dims[2] = {inner, outer};
  cuuint64_t strides[1] = {inner * 2};
  cuuint32_t box[2] = {bi, bo};
  cuuint32_t es[2] = {1, 1};
  fn(m, CU_TENSOR_MAP_DATA_TYPE_BFLOAT16, 2, const_cast<void*>(ptr), dims, strides, box, es, CU_TENSOR_MAP_INTERLEAVE_NONE, swz,
     CU_TENSOR_MAP_L2_PROMOTION_L2_256B, CU_TENSOR_MAP_FLOAT_OOB_FILL_NONE);
}

}

extern "C" void kernel_launch(void* const* d_in, const int* in_sizes, int n_in, void* d_out, int out_size) {
  (void)in_sizes; (void)n_in; (void)out_size;
  const __nv_bfloat16* x = (const __nv_bfloat16*)d_in[0];
  const __nv_bfloat16* mem0 = (const __nv_bfloat16*)d_in[1];
  const void* Wq = d_in[2]; const void* Wk = d_in[3]; const void* Wv = d_in[4]; const void* Wo = d_in[5];
  const void* Wg = d_in[8]; const void* Wu = d_in[9]; const void* Wd = d_in[10];
  const __nv_bfloat16* gw = (const __nv_bfloat16*)d_in[11];

  void* fnp = nullptr;
  cudaDriverEntryPointQueryResult qr;
  cudaGetDriverEntryPoint("cuTensorMapEncodeTiled", &fnp, cudaEnableDefault, &qr);
  EncodeFn fn = (EncodeFn)fnp;
  void *pOx, *pHid;
  cudaGetSymbolAddress(&pOx, gOx);
  cudaGetSymbolAddress(&pHid, gHid);

  const CUtensorMapSwizzle S128 = CU_TENSOR_MAP_SWIZZLE_128B, S64 = CU_TENSOR_MAP_SWIZZLE_64B;
  RecMaps rm;
  make_map(fn, &rm.w[0], Wq, HD, DM, 64, 64, S128);
  make_map(fn, &rm.w[1], Wk, HD, DM, 64, 64, S128);
  make_map(fn, &rm.w[2], Wv, HD, DM, 64, 64, S128);
  make_map(fn, &rm.wo, Wo, DM, HD, 64, 128, S128);
  make_map(fn, &rm.wo_half, Wo, DM, HD, 32, 64, S64);
  {
    cuuint64_t dims[3] = {64, (cuuint64_t)S_LEN, 16};
    cuuint64_t strides[2] = {DM * 2, 128};
    cuuint32_t box[3] = {64, 32, 2};
    cuuint32_t es[3] = {1, 1, 1};
    fn(&rm.x, CU_TENSOR_MAP_DATA_TYPE_BFLOAT16, 3, (void*)x, dims, strides, box, es, CU_TENSOR_MAP_INTERLEAVE_NONE, S128,
       CU_TENSOR_MAP_L2_PROMOTION_L2_256B, CU_TENSOR_MAP_FLOAT_OOB_FILL_NONE);
    box[2] = 1;
    fn(&rm.x1, CU_TENSOR_MAP_DATA_TYPE_BFLOAT16, 3, (void*)x, dims, strides, box, es, CU_TENSOR_MAP_INTERLEAVE_NONE, S128,
       CU_TENSOR_MAP_L2_PROMOTION_L2_256B, CU_TENSOR_MAP_FLOAT_OOB_FILL_NONE);
  }
  make_map(fn, &rm.ox, pOx, HD, S_LEN, 64, 32, S128);
  GemmMaps g1;
  make_map(fn, &g1.a0, x, DM, S_LEN, 64, 128, S128);
  g1.a1 = g1.a0;
  make_map(fn, &g1.b0, Wg, FF, DM, 64, 64, S128);
  make_map(fn, &g1.b1, Wu, FF, DM, 64, 64, S128);
  make_map(fn, &g1.out, pHid, FF, S_LEN, 64, 64, S128);
  GemmMaps g2;
  make_map(fn, &g2.a0, pOx, HD, S_LEN, 64, 128, S128);
  make_map(fn, &g2.a1, pHid, FF, S_LEN, 64, 128, S128);
  make_map(fn, &g2.b0, Wo, DM, HD, 64, 64, S128);
  make_map(fn, &g2.b1, Wd, DM, FF, 64, 64, S128);
  make_map(fn, &g2.out, d_out, DM, S_LEN, 64, 64, S128);

  constexpr int SM1 = G_STAGES * G_STAGE1 + 32768 + 256, SM2 = F_STAGES * F_STAGE + 32768 + 256;
  cudaFuncSetAttribute(rec_kernel, cudaFuncAttributeMaxDynamicSharedMemorySize, REC_SMEM + REC_PROF * 128);
  cudaFuncSetAttribute(ffn1_kernel, cudaFuncAttributeMaxDynamicSharedMemorySize, SM1);
  cudaFuncSetAttribute(fin_kernel, cudaFuncAttributeMaxDynamicSharedMemorySize, SM2);

  rec_kernel<<<96, 384, REC_SMEM + REC_PROF * 128, cudaStreamPerThread>>>(rm, mem0);
  ffn1_kernel<<<132, 384, SM1, cudaStreamPerThread>>>(g1, x, gw);
  fin_kernel<<<128, 384, SM2, cudaStreamPerThread>>>(g2);
}
```

```cpp
#include <cuda_runtime.h>
#include <cuda_bf16.h>
#include <cuda.h>
#include <stdint.h>

#define REC_PROF 0

namespace {

constexpr int S_LEN = 2048, DM = 1024, NH = 32, DH = 128, NMEM = 8, SEG = 32, NSEG = 64, FF = 3584;
constexpr int HD = NH * DH;

__device__ __nv_bfloat16 gOx[S_LEN * HD];
__device__ __nv_bfloat16 gHid[S_LEN * FF];
__device__ __nv_bfloat16 gB[S_LEN * DM];
__device__ float gGate[S_LEN];
enum { SY_QUEUE = 0, SY_GQ = 8, SY_GATE = 16, SY_HID = 32, SY_B = 64, SY_N = 192 };
__device__ unsigned gSync[SY_N];
__device__ uint4 gPart[2 * 64 * 32 * 16];
#define NREP 8
__device__ uint4 gMem[NREP * 4 * 1024];

__device__ __forceinline__ uint32_t smem_u32(const void* p) { return (uint32_t)__cvta_generic_to_shared(p); }
__device__ __forceinline__ uint32_t mapa(uint32_t a, uint32_t r) {
  uint32_t o; asm volatile("mapa.shared::cluster.u32 %0, %1, %2;" : "=r"(o) : "r"(a), "r"(r)); return o;
}
__device__ __forceinline__ void mbar_init(uint32_t bar, uint32_t cnt) {
  asm volatile("mbarrier.init.shared::cta.b64 [%0], %1;" :: "r"(bar), "r"(cnt) : "memory");
}
__device__ __forceinline__ void mbar_arrive(uint32_t bar) {
  asm volatile("mbarrier.arrive.shared::cta.b64 _, [%0];" :: "r"(bar) : "memory");
}
__device__ __forceinline__ void mbar_expect(uint32_t bar, uint32_t bytes) {
  asm volatile("mbarrier.arrive.expect_tx.shared::cta.b64 _, [%0], %1;" :: "r"(bar), "r"(bytes) : "memory");
}
__device__ __forceinline__ bool mbar_try(uint32_t bar, uint32_t parity) {
  uint32_t ok;
  asm volatile("{\n.reg .pred p;\nmbarrier.try_wait.parity.shared::cta.b64 p, [%1], %2;\nselp.u32 %0, 1, 0, p;\n}"
               : "=r"(ok) : "r"(bar), "r"(parity) : "memory");
  return ok != 0;
}
constexpr int SPIN_LIMIT = 1 << 15;
__device__ __forceinline__ void mbar_wait(uint32_t bar, uint32_t parity) {
#pragma unroll 1
  for (int i = 0; i < SPIN_LIMIT; i++) if (mbar_try(bar, parity)) break;
}
__device__ __forceinline__ void gwait(uint32_t bar, uint32_t parity) {
#pragma unroll 1
  for (int i = 0; i < (1 << 22); i++) if (mbar_try(bar, parity)) break;
}
__device__ __forceinline__ void fence_async() { asm volatile("fence.proxy.async.shared::cta;" ::: "memory"); }
__device__ __forceinline__ void bar_sync(int id, int n) { asm volatile("bar.sync %0, %1;" :: "r"(id), "r"(n) : "memory"); }
__device__ __forceinline__ void bar_arrive(int id, int n) { asm volatile("bar.arrive %0, %1;" :: "r"(id), "r"(n) : "memory"); }

__device__ __forceinline__ void tma_load2d(uint32_t dst, const CUtensorMap* tm, int c0, int c1, uint32_t bar) {
  asm volatile("cp.async.bulk.tensor.2d.shared::cluster.global.mbarrier::complete_tx::bytes [%0], [%1, {%3, %4}], [%2];"
               :: "r"(dst), "l"(tm), "r"(bar), "r"(c0), "r"(c1) : "memory");
}
__device__ __forceinline__ void tma_load3d_mc(uint32_t dst, const CUtensorMap* tm, int c0, int c1, int c2, uint32_t bar, uint16_t mask) {
  asm volatile("cp.async.bulk.tensor.3d.shared::cluster.global.mbarrier::complete_tx::bytes.multicast::cluster [%0], [%1, {%3, %4, %5}], [%2], %6;"
               :: "r"(dst), "l"(tm), "r"(bar), "r"(c0), "r"(c1), "r"(c2), "h"(mask) : "memory");
}
__device__ __forceinline__ void mbar_arrive_remote(uint32_t bar) {
  asm volatile("mbarrier.arrive.shared::cluster.b64 _, [%0];" :: "r"(bar) : "memory");
}
__device__ __forceinline__ uint32_t clk() { uint32_t t;
  asm volatile("mov.u32 %0, %%clock;" : "=r"(t) :: "memory")
; return t; }
__device__ __forceinline__ uint32_t phase_bad(const uint4& v, uint32_t ph) {
  uint32_t a, b;
  asm("lop3.b32 %0, %1, %2, %3, 0x7E;" : "=r"(a) : "r"(v.x), "r"(v.y), "r"(ph));
  asm("lop3.b32 %0, %1, %2, %3, 0x7E;" : "=r"(b) : "r"(v.z), "r"(v.w), "r"(ph));
  return (a | b) & 1u;
}
__device__ __forceinline__ bool has_zero(const uint4& v) { return min(min(v.x, v.y), min(v.z, v.w)) == 0; }
__device__ __forceinline__ uint32_t par(int s) { uint32_t r; asm volatile("and.b32 %0, %1, 1;" : "=r"(r) : "r"(s)); return r; }
__device__ __forceinline__ bool elect() {
  uint32_t p;
  asm volatile("{\n.reg .pred p;\nelect.sync _|p, 0xffffffff;\nselp.u32 %0, 1, 0, p;\n}" : "=r"(p));
  return p != 0;
}
__device__ __forceinline__ int rd_head() { int v; asm volatile("mov.u32 %0, %%ctaid.y;" : "=r"(v)); return v; }
__device__ __forceinline__ int rd_rank() { int v; asm volatile("mov.u32 %0, %%ctaid.x;" : "=r"(v)); return v; }
__device__ __forceinline__ int opaque(int t) { asm volatile("" : "+r"(t)); return t; }
#define otid() opaque(tid)
__device__ __forceinline__ float ex2(float x) { float y; asm("ex2.approx.ftz.f32 %0, %1;" : "=f"(y) : "f"(x)); return y; }
__device__ __forceinline__ float rcp(float x) { float y; asm("rcp.approx.ftz.f32 %0, %1;" : "=f"(y) : "f"(x)); return y; }
__device__ __forceinline__ void tma_store2d(const CUtensorMap* tm, uint32_t src, int c0, int c1) {
  asm volatile("cp.async.bulk.tensor.2d.global.shared::cta.bulk_group [%0, {%2, %3}], [%1];"
               :: "l"(tm), "r"(src), "r"(c0), "r"(c1) : "memory");
}
__device__ __forceinline__ void bulk_commit() { asm volatile("cp.async.bulk.commit_group;" ::: "memory"); }
__device__ __forceinline__ void bulk_wait_read0() { asm volatile("cp.async.bulk.wait_group.read 0;" ::: "memory"); }
__device__ __forceinline__ void bulk_wait0() { asm volatile("cp.async.bulk.wait_group 0;" ::: "memory"); }
__device__ __forceinline__ void bulk_s2c(uint32_t dst, uint32_t src, uint32_t bytes, uint32_t bar) {
  asm volatile("cp.async.bulk.shared::cluster.shared::cta.mbarrier::complete_tx::bytes [%0], [%1], %2, [%3];"
               :: "r"(dst), "r"(src), "r"(bytes), "r"(bar) : "memory");
}
__device__ __forceinline__ void st_async32(uint32_t dst, uint32_t v, uint32_t bar) {
  asm volatile("st.async.shared::cluster.mbarrier::complete_tx::bytes.u32 [%0], %1, [%2];" :: "r"(dst), "r"(v), "r"(bar) : "memory");
}
__device__ __forceinline__ void sts32(uint32_t a, uint32_t v) { asm volatile("st.shared.u32 [%0], %1;" :: "r"(a), "r"(v) : "memory"); }
__device__ __forceinline__ void sts128(uint32_t a, uint4 v) {
  asm volatile("st.shared.v4.u32 [%0], {%1,%2,%3,%4};" :: "r"(a), "r"(v.x), "r"(v.y), "r"(v.z), "r"(v.w) : "memory");
}
__device__ __forceinline__ uint4 ld_relaxed128(const void* p) {
  uint4 v;
  asm volatile("ld.relaxed.gpu.global.v4.u32 {%0,%1,%2,%3}, [%4];" : "=r"(v.x), "=r"(v.y), "=r"(v.z), "=r"(v.w) : "l"(p) : "memory");
  return v;
}
__device__ __forceinline__ void st_relaxed128(void* p, uint32_t a, uint32_t b, uint32_t c, uint32_t d) {
  asm volatile("st.relaxed.gpu.global.v4.u32 [%0], {%1,%2,%3,%4};" :: "l"(p), "r"(a), "r"(b), "r"(c), "r"(d) : "memory");
}
__device__ __forceinline__ void st_relaxed64(void* p, uint32_t a, uint32_t b) {
  asm volatile("st.relaxed.gpu.global.v2.u32 [%0], {%1,%2};" :: "l"(p), "r"(a), "r"(b) : "memory");
}
__device__ __forceinline__ uint32_t nz(uint32_t w) { return w == 0 ? 0x80000000u : w; }
__device__ __forceinline__ float bf_lo(uint32_t w) { return __uint_as_float(w << 16); }
__device__ __forceinline__ float bf_hi(uint32_t w) { return __uint_as_float(w & 0xFFFF0000u); }
__device__ __forceinline__ void st_relaxed32(void* p, uint32_t a) {
  asm volatile("st.relaxed.gpu.global.u32 [%0], %1;" :: "l"(p), "r"(a) : "memory");
}
__device__ __forceinline__ uint32_t pack_bf16(float lo, float hi) {
  uint32_t r; asm("cvt.rn.bf16x2.f32 %0, %1, %2;" : "=r"(r) : "f"(hi), "f"(lo)); return r;
}
__device__ __forceinline__ void ldsm4_t(uint32_t* r, uint32_t addr) {
  asm volatile("ldmatrix.sync.aligned.m8n8.x4.trans.shared.b16 {%0,%1,%2,%3}, [%4];"
               : "=r"(r[0]), "=r"(r[1]), "=r"(r[2]), "=r"(r[3]) : "r"(addr) : "memory");
}
__device__ __forceinline__ void ldsm4(uint32_t* r, uint32_t addr) {
  asm volatile("ldmatrix.sync.aligned.m8n8.x4.shared.b16 {%0,%1,%2,%3}, [%4];"
               : "=r"(r[0]), "=r"(r[1]), "=r"(r[2]), "=r"(r[3]) : "r"(addr) : "memory");
}
__device__ __forceinline__ void mma16816(float* d, const uint32_t* a, uint32_t b0, uint32_t b1) {
  asm volatile("mma.sync.aligned.m16n8k16.row.col.f32.bf16.bf16.f32 {%0,%1,%2,%3}, {%4,%5,%6,%7}, {%8,%9}, {%0,%1,%2,%3};"
               : "+f"(d[0]), "+f"(d[1]), "+f"(d[2]), "+f"(d[3]) : "r"(a[0]), "r"(a[1]), "r"(a[2]), "r"(a[3]), "r"(b0), "r"(b1));
}
__device__ __forceinline__ void stsm4_t(uint32_t addr, uint32_t a, uint32_t b, uint32_t c, uint32_t d) {
  asm volatile("stmatrix.sync.aligned.m8n8.x4.trans.shared.b16 [%0], {%1,%2,%3,%4};" :: "r"(addr), "r"(a), "r"(b), "r"(c), "r"(d) : "memory");
}
__device__ __forceinline__ void stsm4(uint32_t addr, uint32_t a, uint32_t b, uint32_t c, uint32_t d) {
  asm volatile("stmatrix.sync.aligned.m8n8.x4.shared.b16 [%0], {%1,%2,%3,%4};" :: "r"(addr), "r"(a), "r"(b), "r"(c), "r"(d) : "memory");
}
__device__ __forceinline__ uint32_t movm_t(uint32_t a) {
  uint32_t d; asm volatile("movmatrix.sync.aligned.m8n8.trans.b16 %0, %1;" : "=r"(d) : "r"(a)); return d;
}

struct Desc { uint32_t base, off, hi; };
__device__ __forceinline__ Desc mkd(uint32_t base, uint32_t boff, uint32_t lbo, uint32_t sbo, uint32_t swz) {
  return Desc{base, (boff >> 4) + ((lbo >> 4) << 16), (sbo >> 4) | (swz << 30)};
}
#define WG_FENCE() asm volatile("wgmma.fence.sync.aligned;" ::: "memory")
#define WG_COMMIT() asm volatile("wgmma.commit_group.sync.aligned;" ::: "memory")
#define WG_WAIT(n) asm volatile("wgmma.wait_group.sync.aligned " #n ";" ::: "memory")

#define ZERO(a, n) _Pragma("unroll") for (int _i = 0; _i < n; _i++) a[_i] = 0.f
#define F4(d, o) "+f"(d[o]), "+f"(d[o + 1]), "+f"(d[o + 2]), "+f"(d[o + 3])
#define F16(d, o) F4(d, o), F4(d, o + 4), F4(d, o + 8), F4(d, o + 12)
#define F64(d, o) F16(d, o), F16(d, o + 16), F16(d, o + 32), F16(d, o + 48)

template <int TB> __device__ __forceinline__ void wg_rs8(float* d, const uint32_t* a, Desc b, int sc) {
  asm volatile("{\n.reg .pred p;\n.reg .b32 lb;\n.reg .b64 db;\nsetp.ne.b32 p, %11, 0;\nadd.u32 lb, %8, %9;\nmov.b64 db, {lb, %10};\n"
               "wgmma.mma_async.sync.aligned.m64n8k16.f32.bf16.bf16 {%0,%1,%2,%3}, {%4,%5,%6,%7}, db, p, 1, 1, %12;\n}"
               : F4(d, 0) : "r"(a[0]), "r"(a[1]), "r"(a[2]), "r"(a[3]), "r"(b.base), "r"(b.off), "r"(b.hi), "r"(sc), "n"(TB));
}
template <int TA, int TB> __device__ __forceinline__ void wg_ss8(float* d, Desc a, Desc b, int sc) {
  asm volatile("{\n.reg .pred p;\n.reg .b32 la, lb;\n.reg .b64 da, db;\nsetp.ne.b32 p, %10, 0;\n"
               "add.u32 la, %4, %5;\nmov.b64 da, {la, %6};\nadd.u32 lb, %7, %8;\nmov.b64 db, {lb, %9};\n"
               "wgmma.mma_async.sync.aligned.m64n8k16.f32.bf16.bf16 {%0,%1,%2,%3}, da, db, p, 1, 1, %11, %12;\n}"
               : F4(d, 0) : "r"(a.base), "r"(a.off), "r"(a.hi), "r"(b.base), "r"(b.off), "r"(b.hi), "r"(sc), "n"(TA), "n"(TB));
}
template <int TB> __device__ __forceinline__ void wg_rs32(float* d, const uint32_t* a, Desc b, int sc) {
  asm volatile("{\n.reg .pred p;\n.reg .b32 lb;\n.reg .b64 db;\nsetp.ne.b32 p, %23, 0;\nadd.u32 lb, %20, %21;\nmov.b64 db, {lb, %22};\n"
               "wgmma.mma_async.sync.aligned.m64n32k16.f32.bf16.bf16 {%0,%1,%2,%3,%4,%5,%6,%7,%8,%9,%10,%11,%12,%13,%14,%15}, {%16,%17,%18,%19}, db, p, 1, 1, %24;\n}"
               : F16(d, 0) : "r"(a[0]), "r"(a[1]), "r"(a[2]), "r"(a[3]), "r"(b.base), "r"(b.off), "r"(b.hi), "r"(sc), "n"(TB));
}
template <int TA, int TB> __device__ __forceinline__ void wg_ss32(float* d, Desc a, Desc b, int sc) {
  asm volatile("{\n.reg .pred p;\n.reg .b32 la, lb;\n.reg .b64 da, db;\nsetp.ne.b32 p, %22, 0;\n"
               "add.u32 la, %16, %17;\nmov.b64 da, {la, %18};\nadd.u32 lb, %19, %20;\nmov.b64 db, {lb, %21};\n"
               "wgmma.mma_async.sync.aligned.m64n32k16.f32.bf16.bf16 {%0,%1,%2,%3,%4,%5,%6,%7,%8,%9,%10,%11,%12,%13,%14,%15}, da, db, p, 1, 1, %23, %24;\n}"
               : F16(d, 0) : "r"(a.base), "r"(a.off), "r"(a.hi), "r"(b.base), "r"(b.off), "r"(b.hi), "r"(sc), "n"(TA), "n"(TB));
}
template <int TA, int TB> __device__ __forceinline__ void wg_ss40(float* d, Desc a, Desc b, int sc) {
  asm volatile("{\n.reg .pred p;\n.reg .b32 la, lb;\n.reg .b64 da, db;\nsetp.ne.b32 p, %26, 0;\n"
               "add.u32 la, %20, %21;\nmov.b64 da, {la, %22};\nadd.u32 lb, %23, %24;\nmov.b64 db, {lb, %25};\n"
               "wgmma.mma_async.sync.aligned.m64n40k16.f32.bf16.bf16 {%0,%1,%2,%3,%4,%5,%6,%7,%8,%9,%10,%11,%12,%13,%14,%15,%16,%17,%18,%19}, da, db, p, 1, 1, %27, %28;\n}"
               : F16(d, 0), F4(d, 16) : "r"(a.base), "r"(a.off), "r"(a.hi), "r"(b.base), "r"(b.off), "r"(b.hi), "r"(sc), "n"(TA), "n"(TB));
}
template <int TA, int TB> __device__ __forceinline__ void wg_ss128(float* d, Desc a, Desc b, int sc) {
  asm volatile("{\n.reg .pred p;\n.reg .b32 la, lb;\n.reg .b64 da, db;\nsetp.ne.b32 p, %70, 0;\n"
               "add.u32 la, %64, %65;\nmov.b64 da, {la, %66};\nadd.u32 lb, %67, %68;\nmov.b64 db, {lb, %69};\n"
               "wgmma.mma_async.sync.aligned.m64n128k16.f32.bf16.bf16 {%0,%1,%2,%3,%4,%5,%6,%7,%8,%9,%10,%11,%12,%13,%14,%15,%16,%17,%18,%19,%20,%21,%22,%23,%24,%25,%26,%27,%28,%29,%30,%31,%32,%33,%34,%35,%36,%37,%38,%39,%40,%41,%42,%43,%44,%45,%46,%47,%48,%49,%50,%51,%52,%53,%54,%55,%56,%57,%58,%59,%60,%61,%62,%63}, da, db, p, 1, 1, %71, %72;\n}"
               : F64(d, 0) : "r"(a.base), "r"(a.off), "r"(a.hi), "r"(b.base), "r"(b.off), "r"(b.hi), "r"(sc), "n"(TA), "n"(TB));
}
template <int TA, int TB> __device__ __forceinline__ void wg_ss256(float* d, Desc a, Desc b, int sc) {
  asm volatile("{\n.reg .pred p;\n.reg .b32 la, lb;\n.reg .b64 da, db;\nsetp.ne.b32 p, %134, 0;\n"
               "add.u32 la, %128, %129;\nmov.b64 da, {la, %130};\nadd.u32 lb, %131, %132;\nmov.b64 db, {lb, %133};\n"
               "wgmma.mma_async.sync.aligned.m64n256k16.f32.bf16.bf16 {%0,%1,%2,%3,%4,%5,%6,%7,%8,%9,%10,%11,%12,%13,%14,%15,%16,%17,%18,%19,%20,%21,%22,%23,%24,%25,%26,%27,%28,%29,%30,%31,%32,%33,%34,%35,%36,%37,%38,%39,%40,%41,%42,%43,%44,%45,%46,%47,%48,%49,%50,%51,%52,%53,%54,%55,%56,%57,%58,%59,%60,%61,%62,%63,%64,%65,%66,%67,%68,%69,%70,%71,%72,%73,%74,%75,%76,%77,%78,%79,%80,%81,%82,%83,%84,%85,%86,%87,%88,%89,%90,%91,%92,%93,%94,%95,%96,%97,%98,%99,%100,%101,%102,%103,%104,%105,%106,%107,%108,%109,%110,%111,%112,%113,%114,%115,%116,%117,%118,%119,%120,%121,%122,%123,%124,%125,%126,%127}, da, db, p, 1, 1, %135, %136;\n}"
               : F64(d, 0), F64(d, 64) : "r"(a.base), "r"(a.off), "r"(a.hi), "r"(b.base), "r"(b.off), "r"(b.hi), "r"(sc), "n"(TA), "n"(TB));
}

constexpr int NRS = 44;
constexpr int NRSC = NRS / 4;
constexpr uint32_t R_SS = 0;
constexpr uint32_t R_POOL = 81920;
constexpr uint32_t R_MRS = R_POOL + 25600;
constexpr uint32_t R_V = 118784;
constexpr uint32_t R_K = 129024;
constexpr uint32_t R_Q = 139264;
constexpr uint32_t R_WO = R_Q + 10240;
constexpr uint32_t R_P0 = R_K + 8192;
constexpr uint32_t R_PX = R_Q + 5120;
constexpr uint32_t R_BAR = 231424;
constexpr uint32_t R_INV = R_BAR + 224;
constexpr uint32_t REC_SMEM = 231680;
enum { B_XFULL = 0, B_SSFULL = 4, B_XDONE = 5, B_PRO = 6, B_SDONE = 7, B_POOL = 8, B_QKV = 9, B_KVX = 10, B_TFREE = 11, B_WSS = 12, B_WO = 13, B_W0 = 14, B_XTILE = 17, B_PUB = 18 };
#define SS_ISSUE -1

struct RecMaps { CUtensorMap w[3]; CUtensorMap wo; CUtensorMap wo_half; CUtensorMap x3; CUtensorMap x2; CUtensorMap x1; CUtensorMap ox; int tune[8]; };

#define PROF(i) do {} while (0)
#define PDUMP() do {} while (0)
#define PVAL(i, v) do {} while (0)
#define PSYNC() do {} while (0)
__device__ constexpr int kDelay[8] = {700, 300, 0, 0, 0, 0, 0, 0};
#define DELAY(i) do { if (kDelay[i] > 0) { unsigned _t0 = clock(); while ((int)(clock() - _t0) < kDelay[i]) {} } } while (0)

__global__ void __cluster_dims__(3, 1, 1) __launch_bounds__(384, 1)
rec_kernel(const __grid_constant__ RecMaps maps, const __nv_bfloat16* __restrict__ mem0, const __nv_bfloat16* __restrict__ xg) {
  extern __shared__ __align__(1024) uint8_t smem[];
  const uint32_t sb = smem_u32(smem);
  const int tid = opaque(threadIdx.x);
  const int wid = __shfl_sync(~0u, tid >> 5, 0), wg = wid >> 2, wp = wid & 3;
  const uint32_t s16 = (sb & 0x3FFFF) >> 4;
  const int h = blockIdx.y, c = blockIdx.x;
  const uint32_t bars = sb + R_BAR;
  auto BAR = [&](int i) { return bars + 8u * i; };
  const uint32_t sWo = sb + R_WO;

  if (tid == 0) {
    for (int i = 0; i < 5; i++) mbar_init(BAR(B_XFULL + i), 1);
    mbar_init(BAR(B_XDONE), 24); mbar_init(BAR(B_XTILE), 24); mbar_init(BAR(B_PUB), 8); mbar_init(BAR(B_PRO), 24); mbar_init(BAR(B_SDONE), 3); mbar_init(BAR(B_POOL), 3);
    mbar_init(BAR(B_QKV), 9); mbar_init(BAR(B_KVX), 1); mbar_init(BAR(B_TFREE), 3);
    mbar_init(BAR(B_WSS), 1); mbar_init(BAR(B_WO), 1);
    for (int i = 0; i < 3; i++) mbar_init(BAR(B_W0 + i), 1);
    asm volatile("fence.mbarrier_init.release.cluster;" ::: "memory");
    fence_async();
    const CUtensorMap* tw = &maps.w[c];
    mbar_expect(BAR(B_W0 + 0), 81920); mbar_expect(BAR(B_W0 + 1), 81920); mbar_expect(BAR(B_W0 + 2), 16384);
    for (int i = 0; i < NRSC; i++) {
      uint32_t dst = i < 5 ? sb + R_SS + i * 16384 : (i < 10 ? sWo + (i - 5) * 16384 : sb + R_POOL);
      uint32_t bar = BAR(B_W0 + i / 5);
      tma_load2d(dst, tw, h * 128, i * 64, bar);
      tma_load2d(dst + 8192, tw, h * 128 + 64, i * 64, bar);
    }
    {
      const uint32_t per = 43776;
      const uint32_t off = (h * 3 + c) * per, tot = S_LEN * DM * 2;
      const uint32_t len = off + per <= tot ? per : tot - off;
      asm volatile("cp.async.bulk.prefetch.L2.global [%0], %1;" :: "l"(reinterpret_cast<const char*>(xg) + off), "r"(len) : "memory");
    }
  }
  if (h == 0 && c == 0 && tid < SY_N) { gSync[tid] = 0; __threadfence(); }
  asm volatile("barrier.cluster.arrive.aligned; barrier.cluster.wait.aligned;" ::: "memory");
  asm volatile("griddepcontrol.launch_dependents;" ::: "memory");

  { constexpr int ROLE = 0; PROF(15); (void)ROLE; }

  if (wg < 2) {
    asm volatile("setmaxnreg.inc.sync.aligned.u32 224;");
    constexpr int ROLE = 0; (void)ROLE;
    uint32_t wa[NRS * 4];
#pragma unroll
    for (int i = 0; i < NRSC; i++) {
      if (i % 5 == 0) mbar_wait(BAR(B_W0 + i / 5), 0);
      uint32_t src = (i < 5 ? sb + R_SS + i * 16384 : (i < 10 ? sWo + (i - 5) * 16384 : sb + R_POOL)) + wg * 8192;
#pragma unroll
      for (int j = 0; j < 4; j++) {
        int k = j * 16 + ((tid >> 4) & 1) * 8 + (tid & 7);
        int mg = wp * 2 + ((tid >> 3) & 1);
        ldsm4_t(&wa[(i * 4 + j) * 4], src + k * 128 + ((mg ^ (k & 7)) << 4));
      }
      if (i == 4 || i == 9 || i == 10) {
        bar_sync(3, 256);
        if (tid == 0) {
          fence_async();
          if (i == 4) {
            mbar_expect(BAR(B_WSS), 81920);
            for (int t = 0; t < 2; t++)
              for (int j = 0; j < 5; j++)
                tma_load2d(sb + R_SS + t * 40960 + j * 8192, &maps.w[c], h * 128 + t * 64, (NRSC + j) * 64, BAR(B_WSS));
          } else if (i == 9) {
            mbar_expect(BAR(B_WO), c == 0 ? 81920 : 90112);
            for (int t = 0; t < 5; t++)
              tma_load2d(sWo + t * 16384, &maps.wo, (t < 4 ? (t >> 1) * 6 + c * 2 + (t & 1) : 12 + c) * 64, h * 128, BAR(B_WO));
            if (c != 0) {
              tma_load2d(sb + R_Q, &maps.wo_half, 928 + c * 32, h * 128, BAR(B_WO));
              tma_load2d(sb + R_Q + 5120, &maps.wo_half, 928 + c * 32, h * 128 + 64, BAR(B_WO));
            }
          } else {
            mbar_arrive_remote(mapa(BAR(B_POOL), 0));
          }
        }
      }
    }
    mbar_wait(BAR(B_WSS), 0);
    const uint32_t aSS = s16 + (R_SS >> 4) + wg * 2560;
#define TBASE (R_Q - rd_rank() * 10240)
    PROF(0);

#pragma unroll 1
    for (int s = -1; s < NSEG; s++) {
      float mr[4];
      ZERO(mr, 4);
      if (tid < 5 && s + 1 < NSEG) mbar_expect(BAR(B_XFULL + tid), tid < 3 ? 12288 : (tid == 3 ? 8192 : 20480));
      if (s >= 0) {
        const int t = otid();
        const uint4* src = gMem + ((h & (NREP - 1)) * 4 + (s & 3)) * 1024 + t;
        if (s == 0) {
#pragma unroll 1
          for (int i = 0; i < 4; i++) {
            const int ch = i * 4 + (t >> 6), n = (t >> 3) & 7;
            sts128(sb + (ch < NRSC ? R_MRS + ch * 1024 : R_POOL + (ch - NRSC) * 5120 + 4096) + (t & 63) * 16,
                   *reinterpret_cast<const uint4*>(mem0 + n * DM + ch * 64 + ((t & 7) ^ n) * 8));
          }
        }
        if (s > 0) mbar_wait(BAR(B_PUB), (s - 1) & 1);
        DELAY(1);
        uint4 v[4];
#pragma unroll
        for (int i = 0; i < 4; i++) v[i] = ld_relaxed128(src + i * 256);
#pragma unroll 1
        for (int it = s > 0 ? 0 : SPIN_LIMIT; it < SPIN_LIMIT; it++) {
          uint32_t mn[4];
#pragma unroll
          for (int i = 0; i < 4; i++) mn[i] = min(min(v[i].x, v[i].y), min(v[i].z, v[i].w));
          if (min(min(mn[0], mn[1]), min(mn[2], mn[3])) != 0) break;
#pragma unroll
          for (int i = 0; i < 4; i++) if (mn[i] == 0) v[i] = ld_relaxed128(src + i * 256);
        }
        const uint32_t d0 = sb + (t & 63) * 16, q = t >> 6;
        const uint32_t ma = sb + R_MRS + (t & 7) * 128 + ((((t >> 3) & 3) ^ (t & 7)) << 4);
        if (s > 0) {
          sts128(d0 + R_MRS + q * 1024, v[0]);
          sts128(d0 + R_MRS + 4096 + q * 1024, v[1]);
          sts128(d0 + (q == 3 ? R_POOL + 4096 : R_MRS + 8192 + q * 1024), v[2]);
          sts128(d0 + R_POOL + 5120 + 4096 + q * 5120, v[3]);
        }
        fence_async();
        PROF(9);
        if (SS_ISSUE >= 0) bar_sync(1, 288); else bar_sync(3, 256);
        float am[12];
        ZERO(am, 12);
        uint32_t bf[2][4];
        ldsm4(bf[0], ma);
#pragma unroll
        for (int j = 0; j < NRS / 2; j++) {
          if (j + 1 < NRS / 2) ldsm4(bf[(j + 1) & 1], (ma ^ (((j + 1) & 1) << 6)) + ((j + 1) >> 1) * 1024);
          mma16816((j & 1) ? am + 4 : mr, &wa[j * 8], bf[j & 1][0], bf[j & 1][1]);
          mma16816((j & 1) ? am + 8 : am, &wa[j * 8 + 4], bf[j & 1][2], bf[j & 1][3]);
        }
#pragma unroll
        for (int e = 0; e < 4; e++) mr[e] = (mr[e] + am[e]) + (am[4 + e] + am[8 + e]);
        PROF(8);
      }
      if (s + 1 < NSEG) mbar_wait(BAR(B_SSFULL), (s + 1) & 1);
      PROF(1);
      float a40[20];
      ZERO(a40, 16);
#pragma unroll
      for (int e = 0; e < 4; e++) a40[16 + e] = mr[e];
      WG_FENCE();
#pragma unroll
      for (int j = 0; j < 20; j++)
        wg_ss40<1, 0>(a40, mkd(aSS, j * 2048, 0, 1024, 1), mkd(s16, R_POOL + (j >> 2) * 5120 + (j & 3) * 32, 0, 1024, 1), 1);
      WG_COMMIT();
      WG_WAIT(0);
      float ax[16];
#pragma unroll
      for (int e = 0; e < 16; e++) ax[e] = a40[e];
      if (s >= 0) {
        PROF(2);
        uint32_t m0 = movm_t(pack_bf16(a40[16], a40[17]));
        uint32_t m1 = movm_t(pack_bf16(a40[18], a40[19]));
        {
          const int ln = otid() & 31, tok = ln >> 2;
          const uint32_t o0 = sb + TBASE + wg * 5120 + 4096 + tok * 128 + (((wp * 2) ^ tok) << 4) + (ln & 3) * 4;
#pragma unroll
          for (int r = 1; r < 3; r++) {
            uint32_t rr = c + r >= 3 ? c + r - 3 : c + r;
            uint32_t dst = mapa(o0, rr), rb = mapa(BAR(B_QKV), rr);
            st_async32(dst, m0, rb);
            st_async32(dst ^ 16, m1, rb);
          }
          sts32(o0, m0);
          sts32(o0 ^ 16, m1);
          fence_async();
          __syncwarp();
          if (elect()) mbar_arrive(BAR(B_QKV));
        }
        if (s == NSEG - 1) break;
      }
      if (elect()) mbar_arrive_remote(mapa(BAR(B_PRO), 0));
      if (c == 0 && tid == 224) {
        mbar_wait(BAR(B_PRO), (s + 1) & 1);
        for (int j = 0; j < 3; j++) tma_load3d_mc(sb + R_POOL + j * 12288, &maps.x3, 0, (s + 1) * SEG, j * 3, BAR(B_XFULL + j), 7);
      }
      __syncwarp();
      if (s >= 0) {
        PROF(3);
        PDUMP();
        bar_sync(7, 384);
        PROF(5);
        DELAY(4);
      }
#pragma unroll
      for (int ch = 0; ch < NRSC; ch++) {
        if (ch % 3 == 0) mbar_wait(BAR(B_XFULL + ch / 3), (s + 1) & 1);
        if (ch == 0) { PROF(13); } else if (ch == 9) { PROF(14); }
        if (ch % 3 == 0 || ch == 7) WG_FENCE();
#pragma unroll
        for (int j = 0; j < 4; j++)
          wg_rs32<0>(ax, &wa[(ch * 4 + j) * 4], mkd(s16, (ch < 9 ? R_POOL + ch * 4096 : R_K + (ch - 9) * 4096) + j * 32, 0, 1024, 1), 1);
        if (ch % 3 == 2 || ch == 6 || ch == 10) WG_COMMIT();
        if (ch == 8) {
          WG_WAIT(1);
          if (elect()) mbar_arrive_remote(mapa(BAR(B_XTILE), 0));
        }
      }
      WG_WAIT(0);
      { const int ln = otid() & 31; if (ln < 3) mbar_arrive_remote(mapa(BAR(B_XDONE), ln)); }
      PROF(6);
      if (s >= 0) mbar_wait(BAR(B_TFREE), s & 1);
      bar_sync(3, 256);
      {
        const int ln = otid() & 31, r = ln & 7, blk = ln >> 3;
        const uint32_t ta = sb + TBASE + wg * 5120 + ((blk >> 1) * 8 + r) * 128 + (((wp * 2 + (blk & 1)) ^ r) << 4);
#pragma unroll
        for (int jj = 0; jj < 2; jj++)
          stsm4_t(ta + jj * 2048, pack_bf16(ax[jj * 8 + 0], ax[jj * 8 + 1]), pack_bf16(ax[jj * 8 + 2], ax[jj * 8 + 3]),
                  pack_bf16(ax[jj * 8 + 4], ax[jj * 8 + 5]), pack_bf16(ax[jj * 8 + 6], ax[jj * 8 + 7]));
        fence_async();
        if (SS_ISSUE < 0) bar_arrive(1, 288);
      }
      PROF(7);
    }
  } else {
    asm volatile("setmaxnreg.dec.sync.aligned.u32 56;");
    constexpr int ROLE = 1; (void)ROLE;
    const float sl2e = 0.08838834764831845f * 1.4426950408889634f;
    if (tid == 256) {
      mbar_expect(BAR(B_QKV), 4096);
      mbar_expect(BAR(B_KVX), c == 0 ? 16384 : 8192);
    }
    if (c == 0 && tid == 352) {
      mbar_wait(BAR(B_POOL), 0);
      for (int j = 0; j < 5; j++) tma_load3d_mc(sb + R_POOL + j * 5120, &maps.x1, 0, 0, NRSC + j, BAR(B_SSFULL), 7);
      tma_load3d_mc(sb + R_K, &maps.x2, 0, 0, 9, BAR(B_XFULL + 3), 7);
      mbar_wait(BAR(B_XTILE), 0);
      for (int j = 0; j < 5; j++) tma_load3d_mc(sb + R_POOL + j * 5120, &maps.x1, 0, SEG, NRSC + j, BAR(B_SSFULL), 7);
    }
    __syncwarp();
#pragma unroll 1
    for (int s = 0; s < NSEG; s++) {
      if (wp == 3) {
        bar_sync(1, 288);
        if (tid < 356) {
          if (rd_rank() != 0) {
            mbar_wait(BAR(B_XDONE), par(s));
            DELAY(2);
            const int t = otid(), c = rd_rank();
            const uint32_t src = sb + R_K + 10240 - c * 10240 + ((t >> 1) & 1) * 5120, r2 = (t & 1) == 0 ? 0u : (uint32_t)(3 - c);
            bulk_s2c(mapa(src, r2), src, 4096, mapa(BAR(B_KVX), r2));
          }
        }
        __syncwarp();
      }
      PROF(2);
      PDUMP();
      if (s > 0 && rd_rank() != 0) {
        DELAY(3);
        const int ln = otid() & 31;
        uint4* z = gPart + ((par(s + 1) * 64 + rd_head() * 2 + rd_rank() - 1) * 32 + (ln >> 2)) * 16 + wp * 4 + (ln & 3);
#pragma unroll
        for (int i = 0; i < 4; i++) st_relaxed128(z + i * 128, 0, 0, 0, 0);
      }
      mbar_wait(BAR(B_KVX), par(s));
      mbar_wait(BAR(B_QKV), par(s));
      PROF(3);
      fence_async();
      float sc[20];
      ZERO(sc, 20);
      WG_FENCE();
#pragma unroll
      for (int j = 0; j < 8; j++) {
        Desc da = mkd(s16, R_Q + (j >> 2) * 5120 + (j & 3) * 32, 0, 1024, 1);
        Desc db = mkd(s16, R_K + (j >> 2) * 5120 + (j & 3) * 32, 0, 1024, 1);
        wg_ss40<0, 0>(sc, da, db, j > 0);
      }
      WG_COMMIT();
      WG_WAIT(0);
      PROF(4);
      const bool more = s + 1 < NSEG;
      float psum = 0.f;
      if (wp == 2) {
        float mx = fmaxf(fmaxf(fmaxf(sc[0], sc[1]), fmaxf(sc[4], sc[5])), fmaxf(fmaxf(sc[8], sc[9]), fmaxf(sc[12], sc[13])));
        mx = fmaxf(mx, fmaxf(sc[16], sc[17]));
        mx = fmaxf(mx, __shfl_xor_sync(~0u, mx, 1));
        mx = fmaxf(mx, __shfl_xor_sync(~0u, mx, 2));
        const float mo = -mx * sl2e;
        uint32_t pk[5];
#pragma unroll
        for (int j = 0; j < 5; j++) pk[j] = pack_bf16(ex2(fmaf(sc[4 * j], sl2e, mo)), ex2(fmaf(sc[4 * j + 1], sl2e, mo)));
        bar_sync(5, 128);
        const uint32_t pa = sb + R_P0 + (otid() & 31) * 4;
#pragma unroll
        for (int j = 0; j < 5; j++) sts32(pa + j * 128, pk[j]);
        sts32(pa + 640, 0);
        fence_async();
#pragma unroll
        for (int j = 0; j < 5; j++) psum += __uint_as_float(pk[j] << 16) + __uint_as_float(pk[j] & 0xFFFF0000u);
      } else {
        bar_arrive(5, 128);
        if (wp == 3) {
          if (tid == 352 && more) {
            mbar_expect(BAR(B_QKV), 4096);
            mbar_expect(BAR(B_KVX), rd_rank() == 0 ? 16384 : 8192);
          }
          __syncwarp();
        }
      }
      PROF(10);
      bar_sync(6, 128);
      PROF(5);
      {
        float om[8];
        ZERO(om, 8);
        WG_FENCE();
#pragma unroll
        for (int tl = 0; tl < 2; tl++)
#pragma unroll
          for (int j = 0; j < 3; j++)
            wg_ss8<1, 0>(om + tl * 4, mkd(s16, R_V + tl * 5120 + j * 2048, 0, 1024, 1), mkd(s16, R_P0 + j * 256, 128, 768, 0), j > 0);
        WG_COMMIT();
        if (wp == 2) {
          psum += __shfl_xor_sync(~0u, psum, 1);
          psum += __shfl_xor_sync(~0u, psum, 2);
          const int t = otid();
          if ((t & 3) == 0) sts32(sb + R_INV + (t & 31), __float_as_uint(rcp(psum)));
        } else if (wp == 3) {
          if (tid == 352 && more) mbar_arrive_remote(mapa(BAR(B_SDONE), 0));
          if (s == 0) mbar_wait(BAR(B_WO), 0);
          __syncwarp();
        } else if (rd_rank() == 0) {
          const uint32_t sa = sb + R_Q + (otid() & 63) * 16;
#pragma unroll
          for (int j = 0; j < 5; j++)
            sts128(sa + (j < 4 ? j * 1024 : 8192), make_uint4(__float_as_uint(sc[j * 4]), __float_as_uint(sc[j * 4 + 1]), __float_as_uint(sc[j * 4 + 2]), __float_as_uint(sc[j * 4 + 3])));
        }
        WG_WAIT(0);
        const uint32_t ob = sb + R_Q + 4096 + wp * 256 + (otid() & 31) * 4;
#pragma unroll
        for (int tl = 0; tl < 2; tl++) {
          sts32(ob + tl * 5120, pack_bf16(om[tl * 4], om[tl * 4 + 1]));
          sts32(ob + tl * 5120 + 128, pack_bf16(om[tl * 4 + 2], om[tl * 4 + 3]));
        }
        fence_async();
      }
      bar_sync(6, 128);
      PROF(6);
      if (more) {
        float i0, i1;
        asm volatile("ld.shared.v2.f32 {%0, %1}, [%2];" : "=f"(i0), "=f"(i1) : "r"(sb + R_INV + (otid() & 3) * 8) : "memory");
        float ao[24];
        ZERO(ao, 24);
        WG_FENCE();
#pragma unroll
        for (int tl = 0; tl < 6; tl++) {
#pragma unroll
          for (int j = 0; j < 8; j++) {
            Desc db = mkd(s16, R_Q + 4096 + (j >> 2) * 5120 + (j & 3) * 256, 128, 128, 0);
            Desc da = tl < 5 ? mkd(s16, R_WO + tl * 16384 + j * 2048, 0, 1024, 1) : mkd(s16, R_Q + (j >> 2) * 5120 + (j & 3) * 1024, 0, 512, 2);
            wg_ss8<1, 1>(ao + tl * 4, da, db, j > 0);
          }
        }
        WG_COMMIT();
        const int ln = otid() & 31, rk = rd_rank();
        char* pbase = reinterpret_cast<char*>(gPart) + (((par(s) * 64 + rk * 8 + wp) * 32 + rd_head()) * 256 + ((ln & 3) * 8 + (ln >> 2)) * 8);
        WG_WAIT(0);
        bar_arrive(7, 384);
#pragma unroll
        for (int tl = 0; tl < 6; tl++) {
          const int cgo = tl < 4 ? (tl >> 1) * 24 + (tl & 1) * 4 : (tl == 4 ? 48 - rk * 4 : 58 - rk * 6);
          if (tl < 5 || (wp < 2 && rk != 0))
            st_relaxed64(pbase + cgo * 8192, nz(pack_bf16(ao[tl * 4] * i0, ao[tl * 4 + 1] * i1)), nz(pack_bf16(ao[tl * 4 + 2] * i0, ao[tl * 4 + 3] * i1)));
        }
      }
      PROF(12);
      if (rd_rank() == 0) {
        if (tid == 352 && more) {
          mbar_wait(BAR(B_SDONE), par(s));
          tma_load3d_mc(sb + R_K, &maps.x2, 0, (s + 1) * SEG, 9, BAR(B_XFULL + 3), 7);
        }
        {
          const int ln = otid() & 31;
          const uint32_t sa = sb + R_Q + ((wp >> 1) * 32 + ln) * 16 + (wp & 1) * 8;
          const int lim = wp * 8 + (ln >> 2) - (ln & 3) * 2;
          float v[10];
#pragma unroll
          for (int j = 0; j < 5; j++)
            asm volatile("ld.shared.v2.f32 {%0, %1}, [%2];" : "=f"(v[2 * j]), "=f"(v[2 * j + 1]) : "r"(sa + (j < 4 ? j * 1024 : 8192)) : "memory");
#pragma unroll
          for (int j = 0; j < 10; j++) v[j] = (j >= 8 || (j >> 1) * 8 + (j & 1) <= lim) ? v[j] * sl2e : -1.4426950408889634e9f;
          float mx = fmaxf(fmaxf(fmaxf(v[0], v[1]), fmaxf(v[2], v[3])), fmaxf(fmaxf(v[4], v[5]), fmaxf(v[6], v[7])));
          mx = fmaxf(mx, fmaxf(v[8], v[9]));
          __syncwarp();
          mx = fmaxf(mx, __shfl_xor_sync(~0u, mx, 1));
          mx = fmaxf(mx, __shfl_xor_sync(~0u, mx, 2));
#pragma unroll
          for (int j = 0; j < 10; j++) v[j] = ex2(v[j] - mx);
          float sum = (((v[0] + v[1]) + (v[2] + v[3])) + ((v[4] + v[5]) + (v[6] + v[7]))) + (v[8] + v[9]);
          sum += __shfl_xor_sync(~0u, sum, 1);
          sum += __shfl_xor_sync(~0u, sum, 2);
          const float inv = rcp(sum);
          const uint32_t pa = sb + R_PX + wp * 768 + ln * 4;
#pragma unroll
          for (int j = 0; j < 5; j++) sts32(pa + j * 128, pack_bf16(v[2 * j] * inv, v[2 * j + 1] * inv));
          sts32(pa + 640, 0);
          fence_async();
          bar_sync(6, 128);
        }
        const int ln = otid() & 31, r = ln & 7, blk = ln >> 3;
        const uint32_t oa = sb + R_Q + ((blk >> 1) * 8 + r) * 128 + (((wp * 2 + (blk & 1)) ^ r) << 4);
#pragma unroll
        for (int tl = 0; tl < 2; tl++) {
          float ox[16];
          ZERO(ox, 16);
          WG_FENCE();
#pragma unroll
          for (int j = 0; j < 3; j++)
            wg_ss32<1, 0>(ox, mkd(s16, R_V + tl * 5120 + j * 2048, 0, 1024, 1), mkd(s16, R_PX + j * 256, 128, 768, 0), j > 0);
          WG_COMMIT();
          WG_WAIT(0);
          if (tl == 1) {
            bar_sync(6, 128);
            if (more && (tid == 289 || tid == 290)) mbar_arrive_remote(mapa(BAR(B_TFREE), tid - 288));
          }
#pragma unroll
          for (int jj = 0; jj < 2; jj++) {
            const float* a = ox + jj * 8;
            stsm4_t(oa + tl * 5120 + jj * 2048, pack_bf16(a[0], a[1]), pack_bf16(a[2], a[3]), pack_bf16(a[4], a[5]), pack_bf16(a[6], a[7]));
          }
        }
        fence_async();
        bar_sync(6, 128);
        if (tid == 256) {
          const int hh = rd_head();
          tma_store2d(&maps.ox, sb + R_Q, hh * 128, s * SEG);
          tma_store2d(&maps.ox, sb + R_Q + 5120, hh * 128 + 64, s * SEG);
          bulk_commit();
          bulk_wait_read0();
          if (more) mbar_arrive(BAR(B_TFREE));
        }
        if (tid == 352 && s + 2 < NSEG) {
          mbar_wait(BAR(B_XTILE), par(s + 1));
          for (int j = 0; j < 5; j++) tma_load3d_mc(sb + R_POOL + j * 5120, &maps.x1, 0, (s + 2) * SEG, NRSC + j, BAR(B_SSFULL), 7);
        }
        __syncwarp();
        PROF(7);
      } else if (more) {
        { int t = otid() - 256; if (t < 3) mbar_arrive_remote(mapa(BAR(B_TFREE), t)); }
        DELAY(0);
        const int ln = otid() & 31, cg = rd_head() * 2 + rd_rank() - 1;
        float a[8];
        {
          const uint4* src = gPart + ((par(s) * 64 + cg) * 32 + (ln >> 2)) * 16 + wp * 4 + (ln & 3);
          uint4 v[4];
#pragma unroll
          for (int i = 0; i < 4; i++) v[i] = ld_relaxed128(src + i * 128);
#pragma unroll 1
          for (int it = 0; it < SPIN_LIMIT; it++) {
            uint32_t mn[4];
#pragma unroll
            for (int i = 0; i < 4; i++) mn[i] = min(min(v[i].x, v[i].y), min(v[i].z, v[i].w));
            if (min(min(mn[0], mn[1]), min(mn[2], mn[3])) != 0) break;
#pragma unroll
            for (int i = 0; i < 4; i++) if (mn[i] == 0) v[i] = ld_relaxed128(src + i * 128);
          }
#define RSUM(fn, f) ((fn(v[0].f) + fn(v[1].f)) + (fn(v[2].f) + fn(v[3].f)))
          a[0] = RSUM(bf_lo, x); a[1] = RSUM(bf_lo, z); a[2] = RSUM(bf_hi, x); a[3] = RSUM(bf_hi, z);
          a[4] = RSUM(bf_lo, y); a[5] = RSUM(bf_lo, w); a[6] = RSUM(bf_hi, y); a[7] = RSUM(bf_hi, w);
#undef RSUM
        }
        __syncwarp();
        PROF(8);
        {
          const bool b2 = (ln & 4) != 0, b3 = (ln & 8) != 0;
          float k[4];
#pragma unroll
          for (int e = 0; e < 4; e++) k[e] = (b2 ? a[4 + e] : a[e]) + __shfl_xor_sync(~0u, b2 ? a[e] : a[4 + e], 4);
          float m0 = (b3 ? k[2] : k[0]) + __shfl_xor_sync(~0u, b3 ? k[0] : k[2], 8);
          float m1 = (b3 ? k[3] : k[1]) + __shfl_xor_sync(~0u, b3 ? k[1] : k[3], 8);
          m0 += __shfl_xor_sync(~0u, m0, 16);
          m1 += __shfl_xor_sync(~0u, m1, 16);
          const uint32_t w = nz(pack_bf16(m0, m1));
          const int n = wp * 2 + ((ln >> 3) & 1), kg = (cg & 3) * 2 + ((ln >> 2) & 1);
          const int off = (cg >> 2) * 256 + n * 32 + ((kg ^ n) << 2) + (ln & 3) + (ln >> 4) * 16384;
          uint32_t* dst = reinterpret_cast<uint32_t*>(gMem) + off;
#pragma unroll
          for (int r = 0; r < NREP / 2; r++) st_relaxed32(dst + ((s + 1) & 3) * 4096 + r * 32768, w);
#pragma unroll
          for (int r = 0; r < NREP / 2; r++) st_relaxed32(dst + ((s + 3) & 3) * 4096 + r * 32768, 0);
          if (ln < 3) mbar_arrive_remote(mapa(BAR(B_PUB), ln));
        }
        PROF(9);
      }
    }
    if (tid == 256) bulk_wait0();
  }
  asm volatile("barrier.cluster.arrive.aligned; barrier.cluster.wait.aligned;" ::: "memory");
}

constexpr int G_STAGES = 4;
constexpr uint32_t G_STAGE = 16384 + 32768;
constexpr int NT_F = 16 * 28, NT_B = 128, NT_A = 128, NT_ALL = NT_F + NT_B + NT_A;
constexpr uint32_t G_SMEM = G_STAGES * G_STAGE + 32768 + 256;

struct GemmMaps { CUtensorMap x, wg, wu, hid_st, hid, wd, b_st, ox, wo, out; };

__device__ __forceinline__ void wait_counter(const unsigned* p, unsigned target) {
#pragma unroll 1
  for (int i = 0; i < (1 << 20); i++) {
    unsigned v;
    asm volatile("ld.acquire.gpu.global.u32 %0, [%1];" : "=r"(v) : "l"(p) : "memory");
    if (v >= target) break;
    __nanosleep(100);
  }
}

__global__ void __launch_bounds__(384, 1)
gemm_kernel(const __grid_constant__ GemmMaps maps, const __nv_bfloat16* __restrict__ x, const __nv_bfloat16* __restrict__ gw) {
  extern __shared__ __align__(1024) uint8_t smem[];
  const uint32_t sb = smem_u32(smem);
  const uint32_t sOut = sb + G_STAGES * G_STAGE;
  const uint32_t bars = sOut + 32768;
  const int tid = threadIdx.x, lane = tid & 31;
  const int wid = __shfl_sync(~0u, tid >> 5, 0), wg = wid >> 2, wp = wid & 3;
  volatile int* stask = reinterpret_cast<volatile int*>(smem + G_STAGES * G_STAGE + 32768 + 128);
  if (tid == 0) {
    for (int i = 0; i < G_STAGES; i++) { mbar_init(bars + 8 * i, 1); mbar_init(bars + 32 + 8 * i, 8); }
    for (int i = 0; i < 2; i++) { mbar_init(bars + 64 + 8 * i, 1); mbar_init(bars + 80 + 8 * i, 8); }
    fence_async();
  }
  __syncthreads();
  if (wg == 2) {
    asm volatile("setmaxnreg.dec.sync.aligned.u32 40;");
    if (wp == 0 && lane == 0) {
      int it = 0;
      bool synced = false;
#pragma unroll 1
      for (int n = 0;; n++) {
        const int task = (int)atomicAdd(&gSync[SY_QUEUE], 1u);
        gwait(bars + 80 + 8 * (n & 1), ((n >> 1) & 1) ^ 1);
        stask[n & 1] = task;
        mbar_arrive(bars + 64 + 8 * (n & 1));
        if (task >= NT_ALL) break;
        const CUtensorMap *ta, *tb;
        int mb, nb, nk;
        if (task < NT_F) { mb = task / 28; nb = task % 28; nk = DM / 64; ta = &maps.x; tb = &maps.wg; }
        else if (task < NT_F + NT_B) {
          mb = (task - NT_F) >> 3; nb = task & 7; nk = FF / 64; ta = &maps.hid; tb = &maps.wd;
          wait_counter(&gSync[SY_HID + mb], 56);
          asm volatile("fence.proxy.async;" ::: "memory");
        } else {
          mb = (task - NT_F - NT_B) >> 3; nb = task & 7; nk = HD / 64; ta = &maps.ox; tb = &maps.wo;
          if (!synced) { asm volatile("griddepcontrol.wait;" ::: "memory"); asm volatile("fence.proxy.async;" ::: "memory"); synced = true; }
        }
#pragma unroll 1
        for (int k = 0; k < nk; k++, it++) {
          const int st = it % G_STAGES;
          gwait(bars + 32 + 8 * st, ((it / G_STAGES) & 1) ^ 1);
          const uint32_t d = sb + st * G_STAGE, fb = bars + 8 * st;
          mbar_expect(fb, task < NT_F ? G_STAGE : 32768u);
          tma_load2d(d, ta, k * 64, mb * 128, fb);
          tma_load2d(d + 16384, tb, nb * 128, k * 64, fb);
          tma_load2d(d + 24576, tb, nb * 128 + 64, k * 64, fb);
          if (task < NT_F) {
            tma_load2d(d + 32768, &maps.wu, nb * 128, k * 64, fb);
            tma_load2d(d + 40960, &maps.wu, nb * 128 + 64, k * 64, fb);
          }
        }
      }
    } else if (wp > 0) {
#pragma unroll 1
      while (true) {
        int blk = 0;
        if (lane == 0) blk = (int)atomicAdd(&gSync[SY_GQ], 1u);
        blk = __shfl_sync(~0u, blk, 0);
        if (blk >= S_LEN / 8) break;
        const int row = blk * 8 + (lane >> 2);
        const uint4* xr = reinterpret_cast<const uint4*>(x + (size_t)row * DM) + (lane & 3);
        const uint4* gr = reinterpret_cast<const uint4*>(gw) + (lane & 3);
        float g = 0.f;
#pragma unroll 2
        for (int i = 0; i < 32; i++) {
          const uint4 a = xr[i * 4], b = gr[i * 4];
          g += bf_lo(a.x) * bf_lo(b.x) + bf_hi(a.x) * bf_hi(b.x) + bf_lo(a.y) * bf_lo(b.y) + bf_hi(a.y) * bf_hi(b.y) +
               bf_lo(a.z) * bf_lo(b.z) + bf_hi(a.z) * bf_hi(b.z) + bf_lo(a.w) * bf_lo(b.w) + bf_hi(a.w) * bf_hi(b.w);
        }
        g += __shfl_xor_sync(~0u, g, 1); g += __shfl_xor_sync(~0u, g, 2);
        if ((lane & 3) == 0) gGate[row] = rcp(1.0f + ex2(g * -1.4426950408889634f));
        __threadfence();
        __syncwarp();
        if (lane == 0) asm volatile("red.release.gpu.global.add.u32 [%0], 1;" :: "l"(&gSync[SY_GATE]) : "memory");
      }
      asm volatile("griddepcontrol.wait;" ::: "memory");
      for (int i = blockIdx.x * 96 + (tid - 288); i < 2 * 64 * 32 * 16; i += gridDim.x * 96) gPart[i] = make_uint4(0, 0, 0, 0);
      for (int i = blockIdx.x * 96 + (tid - 288); i < NREP * 4 * 1024; i += gridDim.x * 96) gMem[i] = make_uint4(0, 0, 0, 0);
    }
  } else {
    asm volatile("setmaxnreg.inc.sync.aligned.u32 232;");
    int it = 0;
    const int r = wg * 64 + wp * 16 + (lane & 7) + ((lane >> 3) & 1) * 8;
#pragma unroll 1
    for (int n = 0;; n++) {
      gwait(bars + 64 + 8 * (n & 1), (n >> 1) & 1);
      const int task = stask[n & 1];
      __syncwarp();
      if (lane == 0) mbar_arrive(bars + 80 + 8 * (n & 1));
      if (task >= NT_ALL) break;
      if (task < NT_F) {
        const int mb = task / 28, nb = task % 28;
        float acc[128];
        ZERO(acc, 128);
#pragma unroll 1
        for (int k = 0; k < DM / 64; k++, it++) {
          const int st = it % G_STAGES;
          gwait(bars + 8 * st, (it / G_STAGES) & 1);
          const uint32_t d16 = ((sb + st * G_STAGE) & 0x3FFFF) >> 4;
          WG_FENCE();
#pragma unroll
          for (int j = 0; j < 4; j++) wg_ss256<0, 1>(acc, mkd(d16 + wg * 512, j * 32, 0, 1024, 1), mkd(d16, 16384 + j * 2048, 8192, 1024, 1), 1);
          WG_COMMIT();
          if (k > 0) { WG_WAIT(1); if (lane == 0) mbar_arrive(bars + 32 + 8 * ((it - 1) % G_STAGES)); }
        }
        WG_WAIT(0);
        if (lane == 0) mbar_arrive(bars + 32 + 8 * ((it - 1) % G_STAGES));
#pragma unroll
        for (int j = 0; j < 8; j++) {
          uint32_t v[4];
#pragma unroll
          for (int q = 0; q < 4; q++) {
            const float g0 = acc[j * 8 + q * 2], g1 = acc[j * 8 + q * 2 + 1];
            const float u0 = acc[64 + j * 8 + q * 2], u1 = acc[64 + j * 8 + q * 2 + 1];
            v[q] = pack_bf16(g0 * rcp(1.0f + ex2(g0 * -1.4426950408889634f)) * u0, g1 * rcp(1.0f + ex2(g1 * -1.4426950408889634f)) * u1);
          }
          const int g = (j & 3) * 2 + (lane >> 4);
          stsm4(sOut + (j >> 2) * 16384 + r * 128 + ((g ^ (r & 7)) << 4), v[0], v[1], v[2], v[3]);
        }
        fence_async();
        bar_sync(1 + wg, 128);
        if ((tid & 127) == 0) {
          tma_store2d(&maps.hid_st, sOut + wg * 8192, nb * 128, mb * 128 + wg * 64);
          tma_store2d(&maps.hid_st, sOut + 16384 + wg * 8192, nb * 128 + 64, mb * 128 + wg * 64);
          bulk_commit();
          bulk_wait0();
          asm volatile("fence.proxy.async;" ::: "memory");
          asm volatile("red.release.gpu.global.add.u32 [%0], 1;" :: "l"(&gSync[SY_HID + mb]) : "memory");
        }
        bar_sync(1 + wg, 128);
      } else {
        const bool isA = task >= NT_F + NT_B;
        const int tile = (task - NT_F) & 127, mb = tile >> 3, nb = tile & 7, nk = isA ? HD / 64 : FF / 64;
        float acc[64];
        ZERO(acc, 64);
#pragma unroll 1
        for (int k = 0; k < nk; k++, it++) {
          const int st = it % G_STAGES;
          gwait(bars + 8 * st, (it / G_STAGES) & 1);
          const uint32_t d16 = ((sb + st * G_STAGE) & 0x3FFFF) >> 4;
          WG_FENCE();
#pragma unroll
          for (int j = 0; j < 4; j++) wg_ss128<0, 1>(acc, mkd(d16 + wg * 512, j * 32, 0, 1024, 1), mkd(d16, 16384 + j * 2048, 8192, 1024, 1), 1);
          WG_COMMIT();
          if (k > 0) { WG_WAIT(1); if (lane == 0) mbar_arrive(bars + 32 + 8 * ((it - 1) % G_STAGES)); }
        }
        const int row = mb * 128 + wg * 64 + wp * 16 + (lane >> 2);
        float g0 = 0.f, g1 = 0.f;
        uint32_t bv[32];
        if (isA) {
          wait_counter(&gSync[SY_GATE], S_LEN / 8);
          g0 = __ldcg(&gGate[row]); g1 = __ldcg(&gGate[row + 8]);
          wait_counter(&gSync[SY_B + tile], 2);
          const uint32_t* bp = reinterpret_cast<const uint32_t*>(gB + (size_t)row * DM + nb * 128) + (lane & 3);
#pragma unroll
          for (int j = 0; j < 16; j++) { bv[2 * j] = __ldcg(bp + j * 4); bv[2 * j + 1] = __ldcg(bp + j * 4 + 8 * DM / 2); }
        }
        WG_WAIT(0);
        if (lane == 0) mbar_arrive(bars + 32 + 8 * ((it - 1) % G_STAGES));
#pragma unroll
        for (int j = 0; j < 8; j++) {
          uint32_t v[4];
#pragma unroll
          for (int q = 0; q < 4; q++) {
            const int i = j * 8 + q * 2;
            if (isA) {
              const float g = (q & 1) ? g1 : g0;
              const uint32_t b = bv[j * 4 + q];
              v[q] = pack_bf16(g * acc[i] + (1.0f - g) * bf_lo(b), g * acc[i + 1] + (1.0f - g) * bf_hi(b));
            } else {
              v[q] = pack_bf16(acc[i], acc[i + 1]);
            }
          }
          const int g = (j & 3) * 2 + (lane >> 4);
          stsm4(sOut + (j >> 2) * 16384 + r * 128 + ((g ^ (r & 7)) << 4), v[0], v[1], v[2], v[3]);
        }
        fence_async();
        bar_sync(1 + wg, 128);
        if ((tid & 127) == 0) {
          const CUtensorMap* to = isA ? &maps.out : &maps.b_st;
          tma_store2d(to, sOut + wg * 8192, nb * 128, mb * 128 + wg * 64);
          tma_store2d(to, sOut + 16384 + wg * 8192, nb * 128 + 64, mb * 128 + wg * 64);
          bulk_commit();
          bulk_wait0();
          if (!isA) {
            asm volatile("fence.proxy.async;" ::: "memory");
            asm volatile("red.release.gpu.global.add.u32 [%0], 1;" :: "l"(&gSync[SY_B + tile]) : "memory");
          }
        }
        bar_sync(1 + wg, 128);
      }
    }
  }
}

typedef CUresult (*EncodeFn)(CUtensorMap*, CUtensorMapDataType, cuuint32_t, void*, const cuuint64_t*, const cuuint64_t*,
                             const cuuint32_t*, const cuuint32_t*, CUtensorMapInterleave, CUtensorMapSwizzle,
                             CUtensorMapL2promotion, CUtensorMapFloatOOBfill);

void make_map(EncodeFn fn, CUtensorMap* m, const void* ptr, uint64_t inner, uint64_t outer, uint32_t bi, uint32_t bo,
              CUtensorMapSwizzle swz) {
  cuuint64_t dims[2] = {inner, outer};
  cuuint64_t strides[1] = {inner * 2};
  cuuint32_t box[2] = {bi, bo};
  cuuint32_t es[2] = {1, 1};
  fn(m, CU_TENSOR_MAP_DATA_TYPE_BFLOAT16, 2, const_cast<void*>(ptr), dims, strides, box, es, CU_TENSOR_MAP_INTERLEAVE_NONE, swz,
     CU_TENSOR_MAP_L2_PROMOTION_L2_256B, CU_TENSOR_MAP_FLOAT_OOB_FILL_NONE);
}

}

extern "C" void kernel_launch(void* const* d_in, const int* in_sizes, int n_in, void* d_out, int out_size) {
  (void)in_sizes; (void)n_in; (void)out_size;
  const __nv_bfloat16* x = (const __nv_bfloat16*)d_in[0];
  const __nv_bfloat16* mem0 = (const __nv_bfloat16*)d_in[1];
  const void* Wq = d_in[2]; const void* Wk = d_in[3]; const void* Wv = d_in[4]; const void* Wo = d_in[5];
  const void* Wg = d_in[8]; const void* Wu = d_in[9]; const void* Wd = d_in[10];
  const __nv_bfloat16* gw = (const __nv_bfloat16*)d_in[11];

  void* fnp = nullptr;
  cudaDriverEntryPointQueryResult qr;
  cudaGetDriverEntryPoint("cuTensorMapEncodeTiled", &fnp, cudaEnableDefault, &qr);
  EncodeFn fn = (EncodeFn)fnp;
  void *pOx, *pHid, *pB;
  cudaGetSymbolAddress(&pB, gB);
  cudaGetSymbolAddress(&pOx, gOx);
  cudaGetSymbolAddress(&pHid, gHid);

  const CUtensorMapSwizzle S128 = CU_TENSOR_MAP_SWIZZLE_128B, S64 = CU_TENSOR_MAP_SWIZZLE_64B;
  RecMaps rm;
  make_map(fn, &rm.w[0], Wq, HD, DM, 64, 64, S128);
  make_map(fn, &rm.w[1], Wk, HD, DM, 64, 64, S128);
  make_map(fn, &rm.w[2], Wv, HD, DM, 64, 64, S128);
  make_map(fn, &rm.wo, Wo, DM, HD, 64, 128, S128);
  make_map(fn, &rm.wo_half, Wo, DM, HD, 32, 64, S64);
  {
    cuuint64_t dims[3] = {64, (cuuint64_t)S_LEN, 16};
    cuuint64_t strides[2] = {DM * 2, 128};
    cuuint32_t box[3] = {64, 32, 2};
    cuuint32_t es[3] = {1, 1, 1};
    fn(&rm.x2, CU_TENSOR_MAP_DATA_TYPE_BFLOAT16, 3, (void*)x, dims, strides, box, es, CU_TENSOR_MAP_INTERLEAVE_NONE, S128,
       CU_TENSOR_MAP_L2_PROMOTION_L2_256B, CU_TENSOR_MAP_FLOAT_OOB_FILL_NONE);
    box[2] = 3;
    fn(&rm.x3, CU_TENSOR_MAP_DATA_TYPE_BFLOAT16, 3, (void*)x, dims, strides, box, es, CU_TENSOR_MAP_INTERLEAVE_NONE, S128,
       CU_TENSOR_MAP_L2_PROMOTION_L2_256B, CU_TENSOR_MAP_FLOAT_OOB_FILL_NONE);
    box[2] = 1;
    fn(&rm.x1, CU_TENSOR_MAP_DATA_TYPE_BFLOAT16, 3, (void*)x, dims, strides, box, es, CU_TENSOR_MAP_INTERLEAVE_NONE, S128,
       CU_TENSOR_MAP_L2_PROMOTION_L2_256B, CU_TENSOR_MAP_FLOAT_OOB_FILL_NONE);
  }
  make_map(fn, &rm.ox, pOx, HD, S_LEN, 64, 32, S128);
  GemmMaps gm;
  make_map(fn, &gm.x, x, DM, S_LEN, 64, 128, S128);
  make_map(fn, &gm.wg, Wg, FF, DM, 64, 64, S128);
  make_map(fn, &gm.wu, Wu, FF, DM, 64, 64, S128);
  make_map(fn, &gm.hid_st, pHid, FF, S_LEN, 64, 64, S128);
  make_map(fn, &gm.hid, pHid, FF, S_LEN, 64, 128, S128);
  make_map(fn, &gm.wd, Wd, DM, FF, 64, 64, S128);
  make_map(fn, &gm.b_st, pB, DM, S_LEN, 64, 64, S128);
  make_map(fn, &gm.ox, pOx, HD, S_LEN, 64, 128, S128);
  make_map(fn, &gm.wo, Wo, DM, HD, 64, 64, S128);
  make_map(fn, &gm.out, d_out, DM, S_LEN, 64, 64, S128);

  cudaFuncSetAttribute(rec_kernel, cudaFuncAttributeMaxDynamicSharedMemorySize, REC_SMEM + (REC_PROF ? 128 : 0));
  cudaFuncSetAttribute(gemm_kernel, cudaFuncAttributeMaxDynamicSharedMemorySize, G_SMEM);

  rec_kernel<<<dim3(3, 32), 384, REC_SMEM + (REC_PROF ? 128 : 0), cudaStreamPerThread>>>(rm, mem0, x);
  {
    cudaLaunchConfig_t cfg = {};
    cfg.gridDim = dim3(132); cfg.blockDim = dim3(384); cfg.dynamicSmemBytes = G_SMEM; cfg.stream = cudaStreamPerThread;
    cudaLaunchAttribute at[1];
    at[0].id = cudaLaunchAttributeProgrammaticStreamSerialization;
    at[0].val.programmaticStreamSerializationAllowed = 1;
    cfg.attrs = at; cfg.numAttrs = 1;
    cudaLaunchKernelEx(&cfg, gemm_kernel, gm, x, gw);
  }
}
```

```cpp
#include <cuda_runtime.h>
#include <cuda_bf16.h>
#include <cuda.h>
#include <stdint.h>

#define REC_PROF 0

namespace {

constexpr int S_LEN = 2048, DM = 1024, NH = 32, DH = 128, NMEM = 8, SEG = 32, NSEG = 64, FF = 3584;
constexpr int HD = NH * DH;

__device__ __nv_bfloat16 gOx[S_LEN * HD];
__device__ __nv_bfloat16 gHid[S_LEN * FF];
__device__ __nv_bfloat16 gB[S_LEN * DM];
__device__ float gGate[S_LEN];
__device__ float4 gTail[128 * 3 * 16 * 256];
enum { SY_QUEUE = 0, SY_GQ = 8, SY_GATE = 16, SY_HID = 32, SY_OX = 48, SY_B = 64, SY_T = 192, SY_N = 320 };
__device__ unsigned gSync[SY_N];
__device__ uint4 gPart[2 * 64 * 32 * 16];
#define NREP 8
__device__ uint4 gMem[NREP * 4 * 1024];

#define TL(i) do {} while (0)
__device__ __forceinline__ uint32_t smem_u32(const void* p) { return (uint32_t)__cvta_generic_to_shared(p); }
__device__ __forceinline__ uint32_t mapa(uint32_t a, uint32_t r) {
  uint32_t o; asm volatile("mapa.shared::cluster.u32 %0, %1, %2;" : "=r"(o) : "r"(a), "r"(r)); return o;
}
__device__ __forceinline__ void mbar_init(uint32_t bar, uint32_t cnt) {
  asm volatile("mbarrier.init.shared::cta.b64 [%0], %1;" :: "r"(bar), "r"(cnt) : "memory");
}
__device__ __forceinline__ void mbar_arrive(uint32_t bar) {
  asm volatile("mbarrier.arrive.shared::cta.b64 _, [%0];" :: "r"(bar) : "memory");
}
__device__ __forceinline__ void mbar_expect(uint32_t bar, uint32_t bytes) {
  asm volatile("mbarrier.arrive.expect_tx.shared::cta.b64 _, [%0], %1;" :: "r"(bar), "r"(bytes) : "memory");
}
__device__ __forceinline__ bool mbar_try(uint32_t bar, uint32_t parity) {
  uint32_t ok;
  asm volatile("{\n.reg .pred p;\nmbarrier.try_wait.parity.shared::cta.b64 p, [%1], %2;\nselp.u32 %0, 1, 0, p;\n}"
               : "=r"(ok) : "r"(bar), "r"(parity) : "memory");
  return ok != 0;
}
constexpr int SPIN_LIMIT = 1 << 15;
__device__ __forceinline__ void mbar_wait(uint32_t bar, uint32_t parity) {
#pragma unroll 1
  for (int i = 0; i < SPIN_LIMIT; i++) if (mbar_try(bar, parity)) break;
}
__device__ __forceinline__ void gwait(uint32_t bar, uint32_t parity) {
#pragma unroll 1
  for (int i = 0; i < (1 << 22); i++) if (mbar_try(bar, parity)) break;
}
__device__ __forceinline__ void fence_async() { asm volatile("fence.proxy.async.shared::cta;" ::: "memory"); }
__device__ __forceinline__ void bar_sync(int id, int n) { asm volatile("bar.sync %0, %1;" :: "r"(id), "r"(n) : "memory"); }
__device__ __forceinline__ void bar_arrive(int id, int n) { asm volatile("bar.arrive %0, %1;" :: "r"(id), "r"(n) : "memory"); }

__device__ __forceinline__ void tma_load2d(uint32_t dst, const CUtensorMap* tm, int c0, int c1, uint32_t bar) {
  asm volatile("cp.async.bulk.tensor.2d.shared::cluster.global.mbarrier::complete_tx::bytes [%0], [%1, {%3, %4}], [%2];"
               :: "r"(dst), "l"(tm), "r"(bar), "r"(c0), "r"(c1) : "memory");
}
__device__ __forceinline__ void tma_load3d_mc(uint32_t dst, const CUtensorMap* tm, int c0, int c1, int c2, uint32_t bar, uint16_t mask) {
  asm volatile("cp.async.bulk.tensor.3d.shared::cluster.global.mbarrier::complete_tx::bytes.multicast::cluster [%0], [%1, {%3, %4, %5}], [%2], %6;"
               :: "r"(dst), "l"(tm), "r"(bar), "r"(c0), "r"(c1), "r"(c2), "h"(mask) : "memory");
}
__device__ __forceinline__ void mbar_arrive_remote(uint32_t bar) {
  asm volatile("mbarrier.arrive.shared::cluster.b64 _, [%0];" :: "r"(bar) : "memory");
}
__device__ __forceinline__ uint32_t clk() { uint32_t t;
  asm volatile("mov.u32 %0, %%clock;" : "=r"(t) :: "memory")
; return t; }
__device__ __forceinline__ uint32_t phase_bad(const uint4& v, uint32_t ph) {
  uint32_t a, b;
  asm("lop3.b32 %0, %1, %2, %3, 0x7E;" : "=r"(a) : "r"(v.x), "r"(v.y), "r"(ph));
  asm("lop3.b32 %0, %1, %2, %3, 0x7E;" : "=r"(b) : "r"(v.z), "r"(v.w), "r"(ph));
  return (a | b) & 1u;
}
__device__ __forceinline__ bool has_zero(const uint4& v) { return min(min(v.x, v.y), min(v.z, v.w)) == 0; }
__device__ __forceinline__ uint32_t par(int s) { uint32_t r; asm volatile("and.b32 %0, %1, 1;" : "=r"(r) : "r"(s)); return r; }
__device__ __forceinline__ bool elect() {
  uint32_t p;
  asm volatile("{\n.reg .pred p;\nelect.sync _|p, 0xffffffff;\nselp.u32 %0, 1, 0, p;\n}" : "=r"(p));
  return p != 0;
}
__device__ __forceinline__ int rd_head() { int v; asm volatile("mov.u32 %0, %%ctaid.y;" : "=r"(v)); return v; }
__device__ __forceinline__ int rd_rank() { int v; asm volatile("mov.u32 %0, %%ctaid.x;" : "=r"(v)); return v; }
template <typename T> __device__ __forceinline__ void pin(T& v) {
  if constexpr (sizeof(T) == 8) asm volatile("" : "+l"(v)); else asm volatile("" : "+r"(v));
}
__device__ __forceinline__ int opaque(int t) { asm volatile("" : "+r"(t)); return t; }
#define otid() opaque(tid)
__device__ __forceinline__ float ex2(float x) { float y; asm("ex2.approx.ftz.f32 %0, %1;" : "=f"(y) : "f"(x)); return y; }
__device__ __forceinline__ float rcp(float x) { float y; asm("rcp.approx.ftz.f32 %0, %1;" : "=f"(y) : "f"(x)); return y; }
__device__ __forceinline__ void tma_prefetch2d(const CUtensorMap* tm, int c0, int c1) {
  asm volatile("cp.async.bulk.prefetch.tensor.2d.L2.global [%0, {%1, %2}];" :: "l"(tm), "r"(c0), "r"(c1) : "memory");
}
__device__ __forceinline__ void tma_store2d(const CUtensorMap* tm, uint32_t src, int c0, int c1) {
  asm volatile("cp.async.bulk.tensor.2d.global.shared::cta.bulk_group [%0, {%2, %3}], [%1];"
               :: "l"(tm), "r"(src), "r"(c0), "r"(c1) : "memory");
}
__device__ __forceinline__ void bulk_commit() { asm volatile("cp.async.bulk.commit_group;" ::: "memory"); }
__device__ __forceinline__ void bulk_wait_read0() { asm volatile("cp.async.bulk.wait_group.read 0;" ::: "memory"); }
__device__ __forceinline__ void bulk_wait0() { asm volatile("cp.async.bulk.wait_group 0;" ::: "memory"); }
__device__ __forceinline__ void bulk_s2c(uint32_t dst, uint32_t src, uint32_t bytes, uint32_t bar) {
  asm volatile("cp.async.bulk.shared::cluster.shared::cta.mbarrier::complete_tx::bytes [%0], [%1], %2, [%3];"
               :: "r"(dst), "r"(src), "r"(bytes), "r"(bar) : "memory");
}
__device__ __forceinline__ void st_async32(uint32_t dst, uint32_t v, uint32_t bar) {
  asm volatile("st.async.shared::cluster.mbarrier::complete_tx::bytes.u32 [%0], %1, [%2];" :: "r"(dst), "r"(v), "r"(bar) : "memory");
}
__device__ __forceinline__ void sts32(uint32_t a, uint32_t v) { asm volatile("st.shared.u32 [%0], %1;" :: "r"(a), "r"(v) : "memory"); }
__device__ __forceinline__ void sts128(uint32_t a, uint4 v) {
  asm volatile("st.shared.v4.u32 [%0], {%1,%2,%3,%4};" :: "r"(a), "r"(v.x), "r"(v.y), "r"(v.z), "r"(v.w) : "memory");
}
__device__ __forceinline__ uint4 ld_relaxed128(const void* p) {
  uint4 v;
  asm volatile("ld.relaxed.gpu.global.v4.u32 {%0,%1,%2,%3}, [%4];" : "=r"(v.x), "=r"(v.y), "=r"(v.z), "=r"(v.w) : "l"(p) : "memory");
  return v;
}
__device__ __forceinline__ void st_relaxed128(void* p, uint32_t a, uint32_t b, uint32_t c, uint32_t d) {
  asm volatile("st.relaxed.gpu.global.v4.u32 [%0], {%1,%2,%3,%4};" :: "l"(p), "r"(a), "r"(b), "r"(c), "r"(d) : "memory");
}
__device__ __forceinline__ void st_relaxed64(void* p, uint32_t a, uint32_t b) {
  asm volatile("st.relaxed.gpu.global.v2.u32 [%0], {%1,%2};" :: "l"(p), "r"(a), "r"(b) : "memory");
}
__device__ __forceinline__ uint32_t nz(uint32_t w) { return w == 0 ? 0x80000000u : w; }
__device__ __forceinline__ float bf_lo(uint32_t w) { return __uint_as_float(w << 16); }
__device__ __forceinline__ float bf_hi(uint32_t w) { return __uint_as_float(w & 0xFFFF0000u); }
__device__ __forceinline__ void st_relaxed32(void* p, uint32_t a) {
  asm volatile("st.relaxed.gpu.global.u32 [%0], %1;" :: "l"(p), "r"(a) : "memory");
}
__device__ __forceinline__ uint32_t pack_bf16(float lo, float hi) {
  uint32_t r; asm("cvt.rn.bf16x2.f32 %0, %1, %2;" : "=r"(r) : "f"(hi), "f"(lo)); return r;
}
__device__ __forceinline__ void ldsm4_t(uint32_t* r, uint32_t addr) {
  asm volatile("ldmatrix.sync.aligned.m8n8.x4.trans.shared.b16 {%0,%1,%2,%3}, [%4];"
               : "=r"(r[0]), "=r"(r[1]), "=r"(r[2]), "=r"(r[3]) : "r"(addr) : "memory");
}
__device__ __forceinline__ void ldsm4(uint32_t* r, uint32_t addr) {
  asm volatile("ldmatrix.sync.aligned.m8n8.x4.shared.b16 {%0,%1,%2,%3}, [%4];"
               : "=r"(r[0]), "=r"(r[1]), "=r"(r[2]), "=r"(r[3]) : "r"(addr) : "memory");
}
__device__ __forceinline__ void mma16816(float* d, const uint32_t* a, uint32_t b0, uint32_t b1) {
  asm volatile("mma.sync.aligned.m16n8k16.row.col.f32.bf16.bf16.f32 {%0,%1,%2,%3}, {%4,%5,%6,%7}, {%8,%9}, {%0,%1,%2,%3};"
               : "+f"(d[0]), "+f"(d[1]), "+f"(d[2]), "+f"(d[3]) : "r"(a[0]), "r"(a[1]), "r"(a[2]), "r"(a[3]), "r"(b0), "r"(b1));
}
__device__ __forceinline__ void mma1688(float* d, uint32_t a0, uint32_t a1, uint32_t b0) {
  asm volatile("mma.sync.aligned.m16n8k8.row.col.f32.bf16.bf16.f32 {%0,%1,%2,%3}, {%4,%5}, {%6}, {%0,%1,%2,%3};"
               : "+f"(d[0]), "+f"(d[1]), "+f"(d[2]), "+f"(d[3]) : "r"(a0), "r"(a1), "r"(b0));
}
__device__ __forceinline__ void lds128(uint32_t* r, uint32_t addr) {
  asm volatile("ld.shared.v4.u32 {%0,%1,%2,%3}, [%4];" : "=r"(r[0]), "=r"(r[1]), "=r"(r[2]), "=r"(r[3]) : "r"(addr) : "memory");
}
__device__ __forceinline__ void stsm4_t(uint32_t addr, uint32_t a, uint32_t b, uint32_t c, uint32_t d) {
  asm volatile("stmatrix.sync.aligned.m8n8.x4.trans.shared.b16 [%0], {%1,%2,%3,%4};" :: "r"(addr), "r"(a), "r"(b), "r"(c), "r"(d) : "memory");
}
__device__ __forceinline__ void stsm4(uint32_t addr, uint32_t a, uint32_t b, uint32_t c, uint32_t d) {
  asm volatile("stmatrix.sync.aligned.m8n8.x4.shared.b16 [%0], {%1,%2,%3,%4};" :: "r"(addr), "r"(a), "r"(b), "r"(c), "r"(d) : "memory");
}
__device__ __forceinline__ uint32_t movm_t(uint32_t a) {
  uint32_t d; asm volatile("movmatrix.sync.aligned.m8n8.trans.b16 %0, %1;" : "=r"(d) : "r"(a)); return d;
}

struct Desc { uint32_t base, off, hi; };
__device__ __forceinline__ Desc mkd(uint32_t base, uint32_t boff, uint32_t lbo, uint32_t sbo, uint32_t swz) {
  return Desc{base, (boff >> 4) + ((lbo >> 4) << 16), (sbo >> 4) | (swz << 30)};
}
#define WG_FENCE() asm volatile("wgmma.fence.sync.aligned;" ::: "memory")
#define WG_COMMIT() asm volatile("wgmma.commit_group.sync.aligned;" ::: "memory")
#define WG_WAIT(n) asm volatile("wgmma.wait_group.sync.aligned " #n ";" ::: "memory")

#define ZERO(a, n) _Pragma("unroll") for (int _i = 0; _i < n; _i++) a[_i] = 0.f
#define F4(d, o) "+f"(d[o]), "+f"(d[o + 1]), "+f"(d[o + 2]), "+f"(d[o + 3])
#define F16(d, o) F4(d, o), F4(d, o + 4), F4(d, o + 8), F4(d, o + 12)
#define F64(d, o) F16(d, o), F16(d, o + 16), F16(d, o + 32), F16(d, o + 48)

template <int TB> __device__ __forceinline__ void wg_rs8(float* d, const uint32_t* a, Desc b, int sc) {
  asm volatile("{\n.reg .pred p;\n.reg .b32 lb;\n.reg .b64 db;\nsetp.ne.b32 p, %11, 0;\nadd.u32 lb, %8, %9;\nmov.b64 db, {lb, %10};\n"
               "wgmma.mma_async.sync.aligned.m64n8k16.f32.bf16.bf16 {%0,%1,%2,%3}, {%4,%5,%6,%7}, db, p, 1, 1, %12;\n}"
               : F4(d, 0) : "r"(a[0]), "r"(a[1]), "r"(a[2]), "r"(a[3]), "r"(b.base), "r"(b.off), "r"(b.hi), "r"(sc), "n"(TB));
}
template <int TA, int TB> __device__ __forceinline__ void wg_ss8(float* d, Desc a, Desc b, int sc) {
  asm volatile("{\n.reg .pred p;\n.reg .b32 la, lb;\n.reg .b64 da, db;\nsetp.ne.b32 p, %10, 0;\n"
               "add.u32 la, %4, %5;\nmov.b64 da, {la, %6};\nadd.u32 lb, %7, %8;\nmov.b64 db, {lb, %9};\n"
               "wgmma.mma_async.sync.aligned.m64n8k16.f32.bf16.bf16 {%0,%1,%2,%3}, da, db, p, 1, 1, %11, %12;\n}"
               : F4(d, 0) : "r"(a.base), "r"(a.off), "r"(a.hi), "r"(b.base), "r"(b.off), "r"(b.hi), "r"(sc), "n"(TA), "n"(TB));
}
template <int TB> __device__ __forceinline__ void wg_rs32(float* d, const uint32_t* a, Desc b, int sc) {
  asm volatile("{\n.reg .pred p;\n.reg .b32 lb;\n.reg .b64 db;\nsetp.ne.b32 p, %23, 0;\nadd.u32 lb, %20, %21;\nmov.b64 db, {lb, %22};\n"
               "wgmma.mma_async.sync.aligned.m64n32k16.f32.bf16.bf16 {%0,%1,%2,%3,%4,%5,%6,%7,%8,%9,%10,%11,%12,%13,%14,%15}, {%16,%17,%18,%19}, db, p, 1, 1, %24;\n}"
               : F16(d, 0) : "r"(a[0]), "r"(a[1]), "r"(a[2]), "r"(a[3]), "r"(b.base), "r"(b.off), "r"(b.hi), "r"(sc), "n"(TB));
}
template <int TA, int TB> __device__ __forceinline__ void wg_ss32(float* d, Desc a, Desc b, int sc) {
  asm volatile("{\n.reg .pred p;\n.reg .b32 la, lb;\n.reg .b64 da, db;\nsetp.ne.b32 p, %22, 0;\n"
               "add.u32 la, %16, %17;\nmov.b64 da, {la, %18};\nadd.u32 lb, %19, %20;\nmov.b64 db, {lb, %21};\n"
               "wgmma.mma_async.sync.aligned.m64n32k16.f32.bf16.bf16 {%0,%1,%2,%3,%4,%5,%6,%7,%8,%9,%10,%11,%12,%13,%14,%15}, da, db, p, 1, 1, %23, %24;\n}"
               : F16(d, 0) : "r"(a.base), "r"(a.off), "r"(a.hi), "r"(b.base), "r"(b.off), "r"(b.hi), "r"(sc), "n"(TA), "n"(TB));
}
template <int TA, int TB> __device__ __forceinline__ void wg_ss40(float* d, Desc a, Desc b, int sc) {
  asm volatile("{\n.reg .pred p;\n.reg .b32 la, lb;\n.reg .b64 da, db;\nsetp.ne.b32 p, %26, 0;\n"
               "add.u32 la, %20, %21;\nmov.b64 da, {la, %22};\nadd.u32 lb, %23, %24;\nmov.b64 db, {lb, %25};\n"
               "wgmma.mma_async.sync.aligned.m64n40k16.f32.bf16.bf16 {%0,%1,%2,%3,%4,%5,%6,%7,%8,%9,%10,%11,%12,%13,%14,%15,%16,%17,%18,%19}, da, db, p, 1, 1, %27, %28;\n}"
               : F16(d, 0), F4(d, 16) : "r"(a.base), "r"(a.off), "r"(a.hi), "r"(b.base), "r"(b.off), "r"(b.hi), "r"(sc), "n"(TA), "n"(TB));
}
template <int TA, int TB> __device__ __forceinline__ void wg_ss128(float* d, Desc a, Desc b, int sc) {
  asm volatile("{\n.reg .pred p;\n.reg .b32 la, lb;\n.reg .b64 da, db;\nsetp.ne.b32 p, %70, 0;\n"
               "add.u32 la, %64, %65;\nmov.b64 da, {la, %66};\nadd.u32 lb, %67, %68;\nmov.b64 db, {lb, %69};\n"
               "wgmma.mma_async.sync.aligned.m64n128k16.f32.bf16.bf16 {%0,%1,%2,%3,%4,%5,%6,%7,%8,%9,%10,%11,%12,%13,%14,%15,%16,%17,%18,%19,%20,%21,%22,%23,%24,%25,%26,%27,%28,%29,%30,%31,%32,%33,%34,%35,%36,%37,%38,%39,%40,%41,%42,%43,%44,%45,%46,%47,%48,%49,%50,%51,%52,%53,%54,%55,%56,%57,%58,%59,%60,%61,%62,%63}, da, db, p, 1, 1, %71, %72;\n}"
               : F64(d, 0) : "r"(a.base), "r"(a.off), "r"(a.hi), "r"(b.base), "r"(b.off), "r"(b.hi), "r"(sc), "n"(TA), "n"(TB));
}
template <int TA, int TB> __device__ __forceinline__ void wg_ss256(float* d, Desc a, Desc b, int sc) {
  asm volatile("{\n.reg .pred p;\n.reg .b32 la, lb;\n.reg .b64 da, db;\nsetp.ne.b32 p, %134, 0;\n"
               "add.u32 la, %128, %129;\nmov.b64 da, {la, %130};\nadd.u32 lb, %131, %132;\nmov.b64 db, {lb, %133};\n"
               "wgmma.mma_async.sync.aligned.m64n256k16.f32.bf16.bf16 {%0,%1,%2,%3,%4,%5,%6,%7,%8,%9,%10,%11,%12,%13,%14,%15,%16,%17,%18,%19,%20,%21,%22,%23,%24,%25,%26,%27,%28,%29,%30,%31,%32,%33,%34,%35,%36,%37,%38,%39,%40,%41,%42,%43,%44,%45,%46,%47,%48,%49,%50,%51,%52,%53,%54,%55,%56,%57,%58,%59,%60,%61,%62,%63,%64,%65,%66,%67,%68,%69,%70,%71,%72,%73,%74,%75,%76,%77,%78,%79,%80,%81,%82,%83,%84,%85,%86,%87,%88,%89,%90,%91,%92,%93,%94,%95,%96,%97,%98,%99,%100,%101,%102,%103,%104,%105,%106,%107,%108,%109,%110,%111,%112,%113,%114,%115,%116,%117,%118,%119,%120,%121,%122,%123,%124,%125,%126,%127}, da, db, p, 1, 1, %135, %136;\n}"
               : F64(d, 0), F64(d, 64) : "r"(a.base), "r"(a.off), "r"(a.hi), "r"(b.base), "r"(b.off), "r"(b.hi), "r"(sc), "n"(TA), "n"(TB));
}

constexpr int NRSC = 11;
#define QCH 2
#define NUE 2
__host__ __device__ constexpr int rs_chunk(int i) { return i == 0 ? 0 : i + NUE; }
__host__ __device__ constexpr int u_chunk(int i) { return i < NUE ? i + 1 : i + 7; }
__host__ __device__ constexpr bool is_u(int ch) { return (ch >= 1 && ch <= NUE) || ch >= 7 + NUE; }
__host__ __device__ constexpr int cls_idx(int ch) { return is_u(ch) ? (ch <= NUE ? ch - 1 : ch - 7) : (ch == 0 ? 0 : ch - NUE); }
constexpr uint32_t R_SS = 0;
constexpr uint32_t R_POOL = 81920;
constexpr uint32_t R_MRS = R_POOL + 25600;
constexpr uint32_t R_V = 118784;
constexpr uint32_t R_K = 129024;
constexpr uint32_t R_Q = 139264;
constexpr uint32_t R_WO = R_Q + 10240;
constexpr uint32_t R_W4 = R_WO + 65536;
constexpr uint32_t R_P0 = R_K + 8192;
constexpr uint32_t R_PX = R_Q + 5120;
constexpr uint32_t R_BAR = 231424;
constexpr uint32_t R_INV = R_BAR + 224;
constexpr uint32_t REC_SMEM = 231680;
enum { B_XFULL = 0, B_SSFULL = 4, B_XDONE = 5, B_PRO = 6, B_SDONE = 7, B_POOL = 8, B_QKV = 9, B_KVX = 10, B_TFREE = 11, B_WSS = 12, B_WO = 13, B_W0 = 14, B_XTILE = 17, B_PUB = 18, B_VX = 19, B_LPUB = 20 };
#define SS_ISSUE 0

struct RecMaps { CUtensorMap w[3]; CUtensorMap wo; CUtensorMap wo_half; CUtensorMap x3; CUtensorMap x2; CUtensorMap x1; CUtensorMap ox; int tune[8]; };

#define PROF(i) do {} while (0)
#define PDUMP() do {} while (0)
#define PVAL(i, v) do {} while (0)
#define PSYNC() do {} while (0)
__device__ constexpr int kDelay[8] = {300, 0, 0, 1000, 0, 0, 0, 0};
#define DELAY(i) do { if (kDelay[i] > 0) { unsigned _t0 = clock(); while ((int)(clock() - _t0) < kDelay[i]) {} } } while (0)

__global__ void __cluster_dims__(3, 1, 1) __launch_bounds__(384, 1)
rec_kernel(const __grid_constant__ RecMaps maps, const __nv_bfloat16* __restrict__ mem0, const __nv_bfloat16* __restrict__ xg) {
  extern __shared__ __align__(1024) uint8_t smem[];
  const uint32_t sb = smem_u32(smem);
  const int tid = opaque(threadIdx.x);
  const int wid = __shfl_sync(~0u, tid >> 5, 0), wg = wid >> 2, wp = wid & 3;
  const uint32_t s16 = (sb & 0x3FFFF) >> 4;
  const int h = blockIdx.y, c = blockIdx.x;
  const uint32_t bars = sb + R_BAR;
  auto BAR = [&](int i) { return bars + 8u * i; };
  const uint32_t sWo = sb + R_WO;

  if (tid == 0 && h == 0 && c == 0) TL(0);
  if (tid == 0) {
    for (int i = 0; i < 5; i++) mbar_init(BAR(B_XFULL + i), 1);
    mbar_init(BAR(B_XDONE), 24); mbar_init(BAR(B_XTILE), 24); mbar_init(BAR(B_PUB), 8); mbar_init(BAR(B_LPUB), 4); mbar_init(BAR(B_VX), c == 2 ? 9 : 1); mbar_init(BAR(B_PRO), 24); mbar_init(BAR(B_SDONE), 2); mbar_init(BAR(B_POOL), 3);
    mbar_init(BAR(B_QKV), c == 2 ? 1 : 9); mbar_init(BAR(B_KVX), 2); mbar_init(BAR(B_TFREE), c == 0 ? 1 : 2);
    mbar_init(BAR(B_WSS), 1); mbar_init(BAR(B_WO), 1);
    for (int i = 0; i < 3; i++) mbar_init(BAR(B_W0 + i), 1);
    asm volatile("fence.mbarrier_init.release.cluster;" ::: "memory");
    fence_async();
    mbar_expect(BAR(B_W0 + 0), 81920); mbar_expect(BAR(B_W0 + 1), 81920); mbar_expect(BAR(B_W0 + 2), 16384);
  }
  if (h == 0 && c == 0 && tid < SY_N) { gSync[tid] = 0; __threadfence(); }
  __syncthreads();
  asm volatile("barrier.cluster.arrive.relaxed.aligned;" ::: "memory");
  asm volatile("griddepcontrol.launch_dependents;" ::: "memory");
  if ((tid & 31) == 0) {
    if (wid < NRSC) {
      const int i = wid;
      const uint32_t dst = i < 5 ? sb + R_SS + i * 16384 : (i < 10 ? sWo + (i - 5) * 16384 : sb + R_POOL);
      const uint32_t bar = BAR(B_W0 + i / 5);
      if (i < 7) {
        tma_load2d(dst, &maps.w[c], h * 128, rs_chunk(i) * 64, bar);
        tma_load2d(dst + 8192, &maps.w[c], h * 128 + 64, rs_chunk(i) * 64, bar);
      } else {
        tma_load2d(dst, &maps.wo, (((i - 7) >> 1) * 6 + c * 2 + ((i - 7) & 1)) * 64, h * 128, bar);
      }
      if (i < 9) {
        const int ch = i < 5 ? NRSC + i : u_chunk(i - 5);
        tma_prefetch2d(&maps.w[c], h * 128, ch * 64);
        tma_prefetch2d(&maps.w[c], h * 128 + 64, ch * 64);
      } else {
        tma_prefetch2d(&maps.wo, i == 9 ? (12 + c) * 64 : 960, h * 128);
      }
    } else {
      const uint32_t per = 43776;
      const uint32_t off = (h * 3 + c) * per, tot = S_LEN * DM * 2;
      const uint32_t len = off + per <= tot ? per : tot - off;
      asm volatile("cp.async.bulk.prefetch.L2.global [%0], %1;" :: "l"(reinterpret_cast<const char*>(xg) + off), "r"(len) : "memory");
    }
  }
  __syncwarp();
  asm volatile("barrier.cluster.wait.aligned;" ::: "memory");

  { constexpr int ROLE = 0; PROF(15); (void)ROLE; }

  const float sl2e = 0.08838834764831845f * 1.4426950408889634f;
  if (wg < 2) {
    asm volatile("setmaxnreg.inc.sync.aligned.u32 224;");
    constexpr int ROLE = 0; (void)ROLE;
    uint32_t wa[28 * 4], wo[16 * 4];
    {
      const uint32_t fo = (((tid >> 4) & 1) * 8 + (tid & 7)) * 128 + (((wp * 2 + ((tid >> 3) & 1)) ^ (tid & 7)) << 4);
#pragma unroll
      for (int i = 0; i < 7; i++) {
        if (i % 5 == 0) mbar_wait(BAR(B_W0 + i / 5), 0);
        const uint32_t src = (i < 5 ? sb + R_SS + i * 16384 : sWo + (i - 5) * 16384) + wg * 8192 + fo;
#pragma unroll
        for (int j = 0; j < 4; j++) ldsm4_t(&wa[(i * 4 + j) * 4], src + j * 2048);
        if (i == 4) {
          bar_sync(3, 256);
          if (tid == 0) {
            fence_async();
            mbar_expect(BAR(B_WSS), 81920);
            for (int t = 0; t < 2; t++)
              for (int j = 0; j < 5; j++)
                tma_load2d(sb + R_SS + t * 40960 + j * 8192, &maps.w[c], h * 128 + t * 64, (NRSC + j) * 64, BAR(B_WSS));
          }
        }
      }
      mbar_wait(BAR(B_W0 + 2), 0);
#pragma unroll
      for (int j = 0; j < 8; j++) {
        ldsm4_t(&wo[j * 4], sWo + (2 + wg) * 16384 + fo + j * 2048);
        ldsm4_t(&wo[32 + j * 4], (wg == 0 ? sWo + 4 * 16384 : sb + R_POOL) + fo + j * 2048);
      }
      bar_sync(3, 256);
      if (tid == 0) {
        fence_async();
        mbar_arrive_remote(mapa(BAR(B_POOL), 0));
        mbar_expect(BAR(B_WO), c == 0 ? 81920 : 90112);
        for (int t = 0; t < 2; t++)
          for (int j = 0; j < 4; j++)
            tma_load2d(sWo + t * 32768 + j * 8192, &maps.w[c], h * 128 + t * 64, u_chunk(j) * 64, BAR(B_WO));
        tma_load2d(sb + R_W4, &maps.wo, (12 + c) * 64, h * 128, BAR(B_WO));
        if (c != 0) {
          tma_load2d(sb + R_Q, &maps.wo_half, 928 + c * 32, h * 128, BAR(B_WO));
          tma_load2d(sb + R_Q + 5120, &maps.wo_half, 928 + c * 32, h * 128 + 64, BAR(B_WO));
        }
      }
    }
    mbar_wait(BAR(B_WSS), 0);
    const uint32_t aSS = s16 + (R_SS >> 4) + wg * 2560;
    const uint32_t aU = s16 + (R_WO >> 4) + wg * 2048;
#define TBASE (R_Q - rd_rank() * 10240)
    PROF(0);
    if (tid == 0 && h == 0 && c == 0) TL(1);
    if (tid == 4) mbar_expect(BAR(B_SSFULL), 20480);
    __syncwarp();
    uint32_t ma = 0;

#pragma unroll 1
    for (int s = -1; s < NSEG; s++) {
      float mr[4];
      ZERO(mr, 4);
      if (s >= 0) {
        float am[12];
        ZERO(am, 12);
        uint32_t bf[4][4];
#pragma unroll
        for (int j = 0; j < 3; j++) ldsm4(bf[j], (ma ^ ((j & 1) << 6)) + rs_chunk(j >> 1) * 1024);
#pragma unroll
        for (int j = 0; j < 14; j++) {
          if (j + 3 < 14) ldsm4(bf[(j + 3) & 3], (ma ^ (((j + 3) & 1) << 6)) + rs_chunk((j + 3) >> 1) * 1024);
          mma16816((j & 1) ? am + 4 : mr, &wa[j * 8], bf[j & 3][0], bf[j & 3][1]);
          mma16816((j & 1) ? am + 8 : am, &wa[j * 8 + 4], bf[j & 3][2], bf[j & 3][3]);
        }
#pragma unroll
        for (int e = 0; e < 4; e++) mr[e] = (mr[e] + am[e]) + (am[4 + e] + am[8 + e]);
        PROF(8);
      }
      PROF(1);
      float a40[20];
      ZERO(a40, 16);
#pragma unroll
      for (int e = 0; e < 4; e++) a40[16 + e] = mr[e];
      float au[4];
      ZERO(au, 4);
      WG_FENCE();
#pragma unroll
      for (int j = 0; j < 16; j++)
        wg_ss8<1, 0>(au, mkd(aU, j * 2048, 0, 1024, 1), mkd(s16, R_MRS + u_chunk(j >> 2) * 1024 + (j & 3) * 32, 0, 1024, 1), 1);
      WG_COMMIT();
      if (s + 1 < NSEG) mbar_wait(BAR(B_SSFULL), (s + 1) & 1);
      WG_FENCE();
#pragma unroll
      for (int j = 0; j < 20; j++)
        wg_ss40<1, 0>(a40, mkd(aSS, j * 2048, 0, 1024, 1), mkd(s16, R_POOL + (j >> 2) * 5120 + (j & 3) * 32, 0, 1024, 1), 1);
      WG_COMMIT();
      uint32_t o0, o1, o2, rb0, rb1, rb2;
      {
        const int ln = otid() & 31, tok = ln >> 2, rk = rd_rank();
        o0 = sb + R_Q - rk * 10240 + wg * 5120 + 4096 + tok * 128 + (((wp * 2) ^ tok) << 4) + (ln & 3) * 4;
        const uint32_t r1 = rk == 2 ? 0 : rk + 1, r2 = rk == 0 ? 2 : rk - 1;
        rb0 = rk == 2 ? BAR(B_VX) : BAR(B_QKV);
        o1 = mapa(o0, r1); o2 = mapa(o0, r2); rb1 = mapa(rb0, r1); rb2 = mapa(rb0, r2);
      }
      WG_WAIT(0);
      float ax[16];
#pragma unroll
      for (int e = 0; e < 16; e++) ax[e] = a40[e];
      if (s >= 0) {
        PROF(2);
        const uint32_t m0 = movm_t(pack_bf16(a40[16] + au[0], a40[17] + au[1]));
        const uint32_t m1 = movm_t(pack_bf16(a40[18] + au[2], a40[19] + au[3]));
        st_async32(o1, m0, rb1);
        st_async32(o2, m0, rb2);
        st_async32(o1 ^ 16, m1, rb1);
        st_async32(o2 ^ 16, m1, rb2);
        sts32(o0, m0);
        sts32(o0 ^ 16, m1);
        __syncwarp();
        if (elect()) mbar_arrive(rb0);
      }
      if (s + 1 < NSEG && elect()) mbar_arrive_remote(mapa(BAR(B_PRO), 0));
      if (s == NSEG - 1) break;
      if (tid < 5 && (tid < 4 || s + 2 < NSEG)) mbar_expect(BAR(B_XFULL + tid), tid < 3 ? 12288 : (tid == 3 ? 8192 : 20480));
      if (c == 0 && tid == 224) {
        mbar_wait(BAR(B_PRO), (s + 1) & 1);
        for (int j = 0; j < 3; j++) tma_load3d_mc(sb + R_POOL + j * 12288, &maps.x3, 0, (s + 1) * SEG, j * 3, BAR(B_XFULL + j), 7);
      }
      __syncwarp();
      if (s < 0) {
        mbar_wait(BAR(B_WO), 0);
      } else {
        PROF(3);
        PDUMP();
        const int ln = otid() & 31;
        uint32_t pdst = (((s & 1) * 64 + rd_rank() * 8 + wg * 4 + wp) * 32 + rd_head()) * 256 + ((ln & 3) * 8 + (ln >> 2)) * 8;
        uint32_t oa = sb + R_Q + 4096 + ln * 16;
        pin(pdst); pin(oa);
        if (wid == 7) {
          bar_sync(5, 160);
          const int rk = rd_rank();
          if (tid == 224 && rk != 0) tma_load3d_mc(sb + R_K, &maps.x2, 0, (s + 1) * SEG, 9, BAR(B_XFULL + 3), (uint16_t)(1 << rk));
          __syncwarp();
        }
        bar_sync(7, 384);
        uint32_t ob[2][4];
        lds128(ob[0], oa);
        lds128(ob[1], oa + 512);
        float a0[4], a1[4];
        ZERO(a0, 4); ZERO(a1, 4);
#pragma unroll
        for (int i = 0; i < 4; i++) {
          mma16816(a0, &wo[i * 8], ob[i & 1][0], ob[i & 1][1]);
          mma16816(a1, &wo[32 + i * 8], ob[i & 1][0], ob[i & 1][1]);
          mma16816(a0, &wo[i * 8 + 4], ob[i & 1][2], ob[i & 1][3]);
          mma16816(a1, &wo[32 + i * 8 + 4], ob[i & 1][2], ob[i & 1][3]);
          if (i < 2) lds128(ob[i & 1], oa + 5120 + i * 512);
        }
        char* pd = reinterpret_cast<char*>(gPart) + pdst;
        st_relaxed64(pd, nz(pack_bf16(a0[0], a0[1])), nz(pack_bf16(a0[2], a0[3])));
        st_relaxed64(pd + 24 * 8192, nz(pack_bf16(a1[0], a1[1])), nz(pack_bf16(a1[2], a1[3])));
        PROF(4);
        mbar_wait(BAR(B_XFULL), (s + 1) & 1);
        bar_sync(9, 384);
        PROF(5);
        DELAY(4);
      }
#pragma unroll
      for (int ch = 0; ch < NRSC; ch++) {
        if (ch % 3 == 0 && (ch > 0 || s < 0)) mbar_wait(BAR(B_XFULL + ch / 3), (s + 1) & 1);
        if (ch == 0) { PROF(13); } else if (ch == 9) { PROF(14); }
        if (ch == 7 + NUE && s >= 0 && rd_rank() != 0) mbar_wait(BAR(B_LPUB), s & 1);
        if (ch % 3 == 0 || ch == 7 + NUE) WG_FENCE();
#pragma unroll
        for (int j = 0; j < 4; j++)
        {
          const Desc db = mkd(s16, (ch < 9 ? R_POOL + ch * 4096 : R_K + (ch - 9) * 4096) + j * 32, 0, 1024, 1);
          if (is_u(ch)) wg_ss32<1, 0>(ax, mkd(aU, (cls_idx(ch) * 4 + j) * 2048, 0, 1024, 1), db, 1);
          else wg_rs32<0>(ax, &wa[(cls_idx(ch) * 4 + j) * 4], db, 1);
        }
        if (ch % 3 == 2 || ch == 10 || ch == 6 + NUE) WG_COMMIT();
      }
      uint4 v[4];
      const uint4* src;
      {
        const int t = otid();
        src = gMem + ((rd_head() & (NREP - 1)) * 4 + ((s + 1) & 3)) * 1024 + t;
        if (s >= 0) {
          mbar_wait(BAR(B_PUB), s & 1);
          DELAY(1);
          PROF(10);
#pragma unroll
          for (int i = 0; i < 4; i++) v[i] = ld_relaxed128(src + i * 256);
        } else {
          const int n = (t >> 3) & 7;
#pragma unroll
          for (int i = 0; i < 4; i++) v[i] = *reinterpret_cast<const uint4*>(mem0 + n * DM + (i * 4 + (t >> 6)) * 64 + ((t & 7) ^ n) * 8);
        }
      }
      WG_WAIT(0);
      { const int ln = otid() & 31; if (ln < 3) mbar_arrive_remote(mapa(BAR(B_XDONE), ln)); }
      PROF(6);
      if (s >= 0 && rd_rank() == 0) mbar_wait(BAR(B_TFREE), s & 1);
      bar_sync(3, 256);
      {
        const int ln = otid() & 31, r = ln & 7, blk = ln >> 3;
        const uint32_t ta = sb + TBASE + wg * 5120 + ((blk >> 1) * 8 + r) * 128 + (((wp * 2 + (blk & 1)) ^ r) << 4);
#pragma unroll
        for (int jj = 0; jj < 2; jj++)
          stsm4_t(ta + jj * 2048, pack_bf16(ax[jj * 8 + 0], ax[jj * 8 + 1]), pack_bf16(ax[jj * 8 + 2], ax[jj * 8 + 3]),
                  pack_bf16(ax[jj * 8 + 4], ax[jj * 8 + 5]), pack_bf16(ax[jj * 8 + 6], ax[jj * 8 + 7]));
      }
      PROF(7);
      {
        const int t = otid();
        const uint32_t q = t >> 6;
        uint32_t d0 = sb + (t & 63) * 16 + R_MRS + q * 1024;
        uint32_t d2 = q == 3 ? d0 - (R_MRS + 3072) + R_POOL + 4096 : d0 + 8192;
        uint32_t d3 = d0 - R_MRS + R_POOL + 5120 + 4096 + q * 4096;
        ma = sb + R_MRS + (t & 7) * 128 + ((((t >> 3) & 3) ^ (t & 7)) << 4);
        pin(d0); pin(d2); pin(d3); pin(ma);
#pragma unroll 1
        for (int it = s >= 0 ? 0 : SPIN_LIMIT - 1; it < SPIN_LIMIT; it++) {
          uint32_t mn[4];
#pragma unroll
          for (int i = 0; i < 4; i++) {
            mn[i] = min(min(v[i].x, v[i].y), min(v[i].z, v[i].w));
            sts128(i < 2 ? d0 + i * 4096 : (i == 2 ? d2 : d3), v[i]);
            if (mn[i] == 0) v[i] = ld_relaxed128(src + i * 256);
          }
          if (__all_sync(~0u, min(min(mn[0], mn[1]), min(mn[2], mn[3])) != 0)) break;
        }
      }
      PROF(11);
      fence_async();
      PROF(9);
      bar_arrive(1, 288);
      bar_sync(3, 256);
    }
  } else {
    asm volatile("setmaxnreg.dec.sync.aligned.u32 56;");
    constexpr int ROLE = 1; (void)ROLE;
    if (tid == 256) {
      mbar_expect(BAR(B_QKV), c == 2 ? 4096 : 2048);
      mbar_expect(BAR(B_KVX), c == 0 ? 16384 : 8192);
      mbar_expect(BAR(B_VX), c == 2 ? 0 : 2048);
    }
    if (c == 0 && tid == 352) {
      mbar_wait(BAR(B_POOL), 0);
      for (int j = 0; j < 5; j++) tma_load3d_mc(sb + R_POOL + j * 5120, &maps.x1, 0, 0, NRSC + j, BAR(B_SSFULL), 7);
      tma_load3d_mc(sb + R_K, &maps.x2, 0, 0, 9, BAR(B_XFULL + 3), 7);
    }
    __syncwarp();
    mbar_wait(BAR(B_WO), 0);
#pragma unroll 1
    for (int s = 0; s < NSEG; s++) {
      if (tid == 320 && s + 1 < NSEG && rd_rank() == 1) {
        mbar_wait(BAR(B_XDONE), par(s));
        DELAY(5);
        for (int j = 0; j < 5; j++) tma_load3d_mc(sb + R_POOL + j * 5120, &maps.x1, 0, (s + 1) * SEG, NRSC + j, BAR(B_SSFULL), 7);
      }
      __syncwarp();
      if (wp == 3) {
        bar_sync(1, 288);
        if (tid == 356) mbar_arrive(BAR(B_KVX));
        if (tid < 356) {
          if (rd_rank() != 0) {
            mbar_wait(BAR(B_XDONE), par(s));
            if (s > 0 && rd_rank() == 2) mbar_wait(BAR(B_TFREE), par(s - 1));
            DELAY(2);
            const int t = otid(), c = rd_rank();
            const uint32_t src = sb + R_K + 10240 - c * 10240 + ((t >> 1) & 1) * 5120, r2 = (t & 1) == 0 ? 0u : (uint32_t)(3 - c);
            bulk_s2c(mapa(src, r2), src, 4096, mapa(BAR(B_KVX), r2));
          }
        }
        __syncwarp();
      }
      PROF(2);
      PDUMP();
      if (s == 1 && tid == 256 && rd_head() == 0 && rd_rank() == 0) TL(2);
      if (s > 0 && rd_rank() != 0) {
        DELAY(3);
        const int ln = otid() & 31;
        uint4* z = gPart + ((par(s + 1) * 64 + rd_head() * 2 + rd_rank() - 1) * 32 + (ln >> 2)) * 16 + wp * 4 + (ln & 3);
#pragma unroll
        for (int i = 0; i < 4; i++) st_relaxed128(z + i * 128, 0, 0, 0, 0);
      }
      const bool more = s + 1 < NSEG;
      mbar_wait(BAR(B_KVX), par(s));
      if (more) {
        uint32_t vx, va, wad, had, po;
        {
          const int ln = otid() & 31;
          vx = sb + R_V + (wp >> 1) * 5120 + (ln & 15) * 128 + ((((wp & 1) * 4 + (ln >> 4)) ^ (ln & 7)) << 4);
          pin(vx);
          va = sb + R_V + (wp >> 1) * 5120 + 4096 + (ln & 7) * 128 + ((((wp & 1) * 4 + (ln >> 3)) ^ (ln & 7)) << 4);
          wad = sb + R_W4 + (((ln >> 4) & 1) * 8 + (ln & 7)) * 128 + (((wp * 2 + ((ln >> 3) & 1)) ^ (ln & 7)) << 4);
          had = sb + R_Q + (((ln >> 4) & 1) * 8 + (ln & 7)) * 64 + (((wp * 2 + ((ln >> 3) & 1)) ^ ((ln >> 1) & 3)) << 4);
          po = ((par(s) * 64 + 48 + rd_rank() * 4 + wp) * 32 + rd_head()) * 256 + ((ln & 3) * 8 + (ln >> 2)) * 8;
          pin(va); pin(wad); pin(had); pin(po);
        }
        mbar_wait(BAR(B_QKV), par(s));
        PROF(3);
        fence_async();
        float sc[20];
        ZERO(sc, 20);
        WG_FENCE();
#pragma unroll
        for (int j = 0; j < 8; j++) {
          Desc da = mkd(s16, R_Q + 4096 + (j >> 2) * 5120 + (j & 3) * 32, 0, 0, 1);
          Desc db = mkd(s16, R_K + (j >> 2) * 5120 + (j & 3) * 32, 0, 1024, 1);
          wg_ss40<0, 0>(sc, da, db, j > 0);
        }
        WG_COMMIT();
        mbar_wait(BAR(B_VX), par(s));
        WG_WAIT(0);
        PROF(4);
        bar_sync(5, 160);
        uint32_t vf[16], vm[4];
#pragma unroll
        for (int i = 0; i < 4; i++) ldsm4_t(vf + i * 4, (vx ^ ((i & 1) << 5)) + (i >> 1) * 2048);
        ldsm4_t(vm, va);
        float mx = fmaxf(fmaxf(fmaxf(sc[0], sc[1]), fmaxf(sc[4], sc[5])), fmaxf(fmaxf(sc[8], sc[9]), fmaxf(sc[12], sc[13])));
        mx = fmaxf(mx, fmaxf(sc[16], sc[17]));
        mx = fmaxf(mx, __shfl_xor_sync(~0u, mx, 1));
        mx = fmaxf(mx, __shfl_xor_sync(~0u, mx, 2));
        const float mo = -mx * sl2e;
        uint32_t pk[5];
#pragma unroll
        for (int j = 0; j < 5; j++) pk[j] = pack_bf16(ex2(fmaf(sc[4 * j], sl2e, mo)), ex2(fmaf(sc[4 * j + 1], sl2e, mo)));
        PROF(10);
        float oc[16];
        ZERO(oc, 16);
#pragma unroll
        for (int t = 0; t < 2; t++) {
          const uint32_t a[4] = {pk[2 * t], 0u, pk[2 * t + 1], 0u};
#pragma unroll
          for (int n = 0; n < 4; n++) mma16816(oc + n * 4, a, vf[t * 8 + n * 2], vf[t * 8 + n * 2 + 1]);
        }
#pragma unroll
        for (int n = 0; n < 4; n++) mma1688(oc + n * 4, pk[4], 0u, vm[n]);
        float psum = ((bf_lo(pk[0]) + bf_hi(pk[0])) + (bf_lo(pk[1]) + bf_hi(pk[1]))) + ((bf_lo(pk[2]) + bf_hi(pk[2])) + (bf_lo(pk[3]) + bf_hi(pk[3]))) + (bf_lo(pk[4]) + bf_hi(pk[4]));
        psum += __shfl_xor_sync(~0u, psum, 1);
        psum += __shfl_xor_sync(~0u, psum, 2);
        const float inv = rcp(psum);
        const uint32_t oa = sb + R_Q + 4096 + (otid() & 31) * 16;
        sts128(oa + (wp >> 1) * 5120 + (wp & 1) * 512,
               make_uint4(pack_bf16(oc[0] * inv, oc[1] * inv), pack_bf16(oc[4] * inv, oc[5] * inv), pack_bf16(oc[8] * inv, oc[9] * inv), pack_bf16(oc[12] * inv, oc[13] * inv)));
        bar_arrive(7, 384);
        const bool second = wp < 2 && rd_rank() != 0;
        uint32_t af[16];
#pragma unroll
        for (int j = 0; j < 4; j++) ldsm4_t(af + j * 4, wad + j * 2048);
        PROF(6);
        bar_sync(6, 128);
        uint32_t ob[4][4];
#pragma unroll
        for (int i = 0; i < 4; i++) lds128(ob[i], oa + (i >> 1) * 5120 + (i & 1) * 512);
        float a0[4], a1[4];
        ZERO(a0, 4); ZERO(a1, 4);
#pragma unroll
        for (int j = 0; j < 8; j++) {
          mma16816((j & 1) ? a1 : a0, af + (j & 3) * 4, ob[j >> 1][(j & 1) * 2], ob[j >> 1][(j & 1) * 2 + 1]);
          if (j < 4) ldsm4_t(af + j * 4, wad + (j + 4) * 2048);
          else if (second) ldsm4_t(af + (j & 3) * 4, had + (j & 3) * 1024);
        }
        st_relaxed64(reinterpret_cast<char*>(gPart) + po, nz(pack_bf16(a0[0] + a1[0], a0[1] + a1[1])), nz(pack_bf16(a0[2] + a1[2], a0[3] + a1[3])));
        if (second) {
          ZERO(a0, 4); ZERO(a1, 4);
#pragma unroll
          for (int j = 0; j < 8; j++) {
            mma16816((j & 1) ? a1 : a0, af + (j & 3) * 4, ob[j >> 1][(j & 1) * 2], ob[j >> 1][(j & 1) * 2 + 1]);
            if (j < 4) ldsm4_t(af + j * 4, had + 5120 + j * 1024);
          }
          st_relaxed64(reinterpret_cast<char*>(gPart) + po + (10 - rd_rank() * 2) * 8192, nz(pack_bf16(a0[0] + a1[0], a0[1] + a1[1])), nz(pack_bf16(a0[2] + a1[2], a0[3] + a1[3])));
        }
        if (rd_rank() != 0) bar_arrive(9, 384);
        if (tid == 352) {
          const int rk = rd_rank();
          mbar_expect(BAR(B_QKV), rk == 2 ? 4096 : 2048);
          mbar_expect(BAR(B_KVX), rk == 0 ? 16384 : 8192);
          mbar_expect(BAR(B_VX), rk == 2 ? 0 : 2048);
          if (rk == 1) mbar_arrive_remote(mapa(BAR(B_TFREE), 2));
        }
        __syncwarp();
      } else {
        mbar_wait(BAR(B_QKV), par(s));
        mbar_wait(BAR(B_VX), par(s));
      }
      PROF(12);
      if (rd_rank() == 0) {
        fence_async();
        {
          float sc[20];
          ZERO(sc, 20);
          WG_FENCE();
#pragma unroll
          for (int j = 0; j < 8; j++)
            wg_ss40<0, 0>(sc, mkd(s16, R_Q + (j >> 2) * 5120 + (j & 3) * 32, 0, 1024, 1), mkd(s16, R_K + (j >> 2) * 5120 + (j & 3) * 32, 0, 1024, 1), j > 0);
          WG_COMMIT();
          if (more) bar_arrive(9, 384);
          WG_WAIT(0);
          bar_sync(6, 128);
          if (wp < 2) {
            const int ln = otid() & 31;
            const uint32_t pa = sb + R_PX + wp * 1536 + ln * 4;
            float mx[2], sum[2];
#pragma unroll
            for (int hf = 0; hf < 2; hf++) {
              const int lim = wp * 16 + hf * 8 + (ln >> 2) - (ln & 3) * 2;
              mx[hf] = -3.0e38f;
#pragma unroll
              for (int j = 0; j < 10; j++) {
                float& v = sc[(j >> 1) * 4 + hf * 2 + (j & 1)];
                v = (j >= 8 || (j >> 1) * 8 + (j & 1) <= lim) ? v * sl2e : -1.4426950408889634e9f;
                mx[hf] = fmaxf(mx[hf], v);
              }
            }
#pragma unroll
            for (int o = 1; o <= 2; o <<= 1) { mx[0] = fmaxf(mx[0], __shfl_xor_sync(~0u, mx[0], o)); mx[1] = fmaxf(mx[1], __shfl_xor_sync(~0u, mx[1], o)); }
#pragma unroll
            for (int hf = 0; hf < 2; hf++) {
              sum[hf] = 0.f;
#pragma unroll
              for (int j = 0; j < 10; j++) { float& v = sc[(j >> 1) * 4 + hf * 2 + (j & 1)]; v = ex2(v - mx[hf]); sum[hf] += v; }
            }
#pragma unroll
            for (int o = 1; o <= 2; o <<= 1) { sum[0] += __shfl_xor_sync(~0u, sum[0], o); sum[1] += __shfl_xor_sync(~0u, sum[1], o); }
#pragma unroll
            for (int hf = 0; hf < 2; hf++) {
              const float inv = rcp(sum[hf]);
#pragma unroll
              for (int j = 0; j < 5; j++) sts32(pa + hf * 768 + j * 128, pack_bf16(sc[j * 4 + hf * 2] * inv, sc[j * 4 + hf * 2 + 1] * inv));
              sts32(pa + hf * 768 + 640, 0);
            }
            fence_async();
          } else if (tid == 352 && more) {
            tma_load3d_mc(sb + R_K, &maps.x2, 0, (s + 1) * SEG, 9, BAR(B_XFULL + 3), 1);
          }
          __syncwarp();
        }
        bar_sync(6, 128);
        const int ln = otid() & 31, r = ln & 7, blk = ln >> 3;
        const uint32_t oa = sb + R_V + ((blk >> 1) * 8 + r) * 128 + (((wp * 2 + (blk & 1)) ^ r) << 4);
#pragma unroll
        for (int tl = 0; tl < 2; tl++) {
          float ox[16];
          ZERO(ox, 16);
          WG_FENCE();
#pragma unroll
          for (int j = 0; j < 3; j++)
            wg_ss32<1, 0>(ox, mkd(s16, R_V + tl * 5120 + j * 2048, 0, 1024, 1), mkd(s16, R_PX + j * 256, 128, 768, 0), j > 0);
          WG_COMMIT();
          WG_WAIT(0);
          bar_sync(6, 128);
          if (tl == 1 && more && tid == 288) mbar_arrive(BAR(B_TFREE));
#pragma unroll
          for (int jj = 0; jj < 2; jj++) {
            const float* a = ox + jj * 8;
            stsm4_t(oa + tl * 5120 + jj * 2048, pack_bf16(a[0], a[1]), pack_bf16(a[2], a[3]), pack_bf16(a[4], a[5]), pack_bf16(a[6], a[7]));
          }
        }
        fence_async();
        bar_sync(6, 128);
        if (tid == 256) {
          const int hh = rd_head();
          tma_store2d(&maps.ox, sb + R_V, hh * 128, s * SEG);
          tma_store2d(&maps.ox, sb + R_V + 5120, hh * 128 + 64, s * SEG);
          bulk_commit();
          bulk_wait_read0();
          if (more) mbar_arrive_remote(mapa(BAR(B_TFREE), 2));
          bulk_wait0();
          asm volatile("fence.proxy.async;" ::: "memory");
          asm volatile("red.release.gpu.global.add.u32 [%0], 1;" :: "l"(&gSync[SY_OX + (s >> 2)]) : "memory");
        }
        __syncwarp();
        PROF(7);
      } else if (more) {
        const int ln = otid() & 31, cg = rd_head() * 2 + rd_rank() - 1;
        const int n = wp * 2 + ((ln >> 3) & 1), kg = (cg & 3) * 2 + ((ln >> 2) & 1);
        uint32_t* dst = reinterpret_cast<uint32_t*>(gMem) + ((cg >> 2) * 256 + n * 32 + ((kg ^ n) << 2) + (ln & 3) + (ln >> 4) * 16384);
        uint32_t* dpub = dst + ((s + 1) & 3) * 4096;
        const uint4* src = gPart + ((par(s) * 64 + cg) * 32 + (ln >> 2)) * 16 + wp * 4 + (ln & 3);
        uint32_t pubbar = ln < 3 ? mapa(BAR(B_PUB), ln) : mapa(BAR(B_LPUB), rd_rank());
        pin(dpub); pin(src); pin(pubbar);
        DELAY(0);
        PROF(11);
        float a[8];
        {
          uint4 v[4];
#pragma unroll
          for (int i = 0; i < 4; i++) v[i] = ld_relaxed128(src + i * 128);
#pragma unroll 1
          for (int it = 0; it < SPIN_LIMIT; it++) {
            uint32_t mn[4];
            ZERO(a, 8);
#pragma unroll
            for (int i = 0; i < 4; i++) {
              mn[i] = min(min(v[i].x, v[i].y), min(v[i].z, v[i].w));
              a[0] += bf_lo(v[i].x); a[1] += bf_lo(v[i].z); a[2] += bf_hi(v[i].x); a[3] += bf_hi(v[i].z);
              a[4] += bf_lo(v[i].y); a[5] += bf_lo(v[i].w); a[6] += bf_hi(v[i].y); a[7] += bf_hi(v[i].w);
              asm volatile("" : "+f"(a[0]), "+f"(a[1]), "+f"(a[2]), "+f"(a[3]), "+f"(a[4]), "+f"(a[5]), "+f"(a[6]), "+f"(a[7]));
              if (mn[i] == 0) v[i] = ld_relaxed128(src + i * 128);
            }
            if (__all_sync(~0u, min(min(mn[0], mn[1]), min(mn[2], mn[3])) != 0)) break;
          }
        }
        __syncwarp();
        PROF(8);
        {
          const bool b2 = (ln & 4) != 0, b3 = (ln & 8) != 0;
          float k[4];
#pragma unroll
          for (int e = 0; e < 4; e++) k[e] = (b2 ? a[4 + e] : a[e]) + __shfl_xor_sync(~0u, b2 ? a[e] : a[4 + e], 4);
          float m0 = (b3 ? k[2] : k[0]) + __shfl_xor_sync(~0u, b3 ? k[0] : k[2], 8);
          float m1 = (b3 ? k[3] : k[1]) + __shfl_xor_sync(~0u, b3 ? k[1] : k[3], 8);
          m0 += __shfl_xor_sync(~0u, m0, 16);
          m1 += __shfl_xor_sync(~0u, m1, 16);
          const uint32_t w = nz(pack_bf16(m0, m1));
#pragma unroll
          for (int r = 0; r < NREP / 2; r++) st_relaxed32(dpub + r * 32768, w);
          if (ln < 4) mbar_arrive_remote(pubbar);
#pragma unroll
          for (int r = 0; r < NREP / 2; r++) st_relaxed32(dst + ((s + 3) & 3) * 4096 + r * 32768, 0);
        }
        PROF(9);
      }
    }
    if (tid == 256) bulk_wait0();
    if (tid == 256 && rd_head() == 0 && rd_rank() == 0) TL(3);
  }
  asm volatile("barrier.cluster.arrive.aligned; barrier.cluster.wait.aligned;" ::: "memory");
}

constexpr int G_STAGES = 4;
constexpr uint32_t G_STAGE = 16384 + 32768;
#define TA1 64
#define TA2 64
constexpr int NT_F = 16 * 28, NT_B = 128, NT_A = TA1 + 2 * TA2 + 4 * (128 - TA1 - TA2), NT_ALL = NT_F + NT_B + NT_A;
__device__ __forceinline__ void decode_a(int t, int& tile, int& part, int& lg) {
  if (t < TA1) { tile = t; part = 0; lg = 0; }
  else if (t < TA1 + 2 * TA2) { tile = TA1 + ((t - TA1) >> 1); part = (t - TA1) & 1; lg = 1; }
  else { tile = TA1 + TA2 + ((t - TA1 - 2 * TA2) >> 2); part = (t - TA1 - 2 * TA2) & 3; lg = 2; }
}
constexpr uint32_t G_SMEM = G_STAGES * G_STAGE + 32768 + 256;

struct GemmMaps { CUtensorMap x, wg, wu, hid_st, hid, wd, b_st, ox, wo, out; };

__device__ __forceinline__ void wait_counter(const unsigned* p, unsigned target) {
#pragma unroll 1
  for (int i = 0; i < (1 << 20); i++) {
    unsigned v;
    asm volatile("ld.acquire.gpu.global.u32 %0, [%1];" : "=r"(v) : "l"(p) : "memory");
    if (v >= target) break;
    __nanosleep(40);
  }
}

__global__ void __launch_bounds__(384, 1)
gemm_kernel(const __grid_constant__ GemmMaps maps, const __nv_bfloat16* __restrict__ x, const __nv_bfloat16* __restrict__ gw) {
  extern __shared__ __align__(1024) uint8_t smem[];
  const uint32_t sb = smem_u32(smem);
  const uint32_t sOut = sb + G_STAGES * G_STAGE;
  const uint32_t bars = sOut + 32768;
  const int tid = threadIdx.x, lane = tid & 31;
  const int wid = __shfl_sync(~0u, tid >> 5, 0), wg = wid >> 2, wp = wid & 3;
  volatile int* stask = reinterpret_cast<volatile int*>(smem + G_STAGES * G_STAGE + 32768 + 128);
  if (tid == 0) {
    for (int i = 0; i < G_STAGES; i++) { mbar_init(bars + 8 * i, 1); mbar_init(bars + 32 + 8 * i, 8); }
    for (int i = 0; i < 2; i++) { mbar_init(bars + 64 + 8 * i, 1); mbar_init(bars + 80 + 8 * i, 8); mbar_init(bars + 96 + 8 * i, 1); }
    fence_async();
  }
  __syncthreads();
  if (wg == 2) {
    asm volatile("setmaxnreg.dec.sync.aligned.u32 40;");
    if (wp == 0 && lane == 0) {
      int it = 0;
#pragma unroll 1
      for (int n = 0;; n++) {
        const int task = (int)atomicAdd(&gSync[SY_QUEUE], 1u);
        if (task >= NT_F + NT_B && task < NT_ALL) {
          int tile, part, lg;
          decode_a(task - NT_F - NT_B, tile, part, lg);
          wait_counter(&gSync[SY_GATE], S_LEN / 8);
          wait_counter(&gSync[SY_B + tile], 2);
        }
        gwait(bars + 80 + 8 * (n & 1), ((n >> 1) & 1) ^ 1);
        if (task <= NT_ALL) TL(16 + task);
        if (n == 0) TL(1800 + blockIdx.x);
        stask[n & 1] = task;
        mbar_arrive(bars + 64 + 8 * (n & 1));
        if (task >= NT_ALL) break;
        const CUtensorMap *ta, *tb;
        int mb, nb, nk, k0 = 0;
        if (task < NT_F) { mb = task / 28; nb = task % 28; nk = DM / 64; ta = &maps.x; tb = &maps.wg; }
        else if (task < NT_F + NT_B) {
          mb = (task - NT_F) >> 3; nb = task & 7; nk = FF / 64; ta = &maps.hid; tb = &maps.wd;
          wait_counter(&gSync[SY_HID + mb], 56);
          asm volatile("fence.proxy.async;" ::: "memory");
        } else {
          int tile, part, lg;
          decode_a(task - NT_F - NT_B, tile, part, lg);
          mb = tile >> 3; nb = tile & 7; nk = (HD / 64) >> lg; k0 = part * nk;
          ta = &maps.ox; tb = &maps.wo;
          wait_counter(&gSync[SY_OX + mb], 4 * NH);
          asm volatile("fence.proxy.async;" ::: "memory");
        }
#pragma unroll 1
        for (int k = 0; k < nk; k++, it++) {
          const int st = it % G_STAGES;
          gwait(bars + 32 + 8 * st, ((it / G_STAGES) & 1) ^ 1);
          const uint32_t d = sb + st * G_STAGE, fb = bars + 8 * st;
          mbar_expect(fb, task < NT_F ? G_STAGE : 32768u);
          tma_load2d(d, ta, (k0 + k) * 64, mb * 128, fb);
          tma_load2d(d + 16384, tb, nb * 128, (k0 + k) * 64, fb);
          tma_load2d(d + 24576, tb, nb * 128 + 64, (k0 + k) * 64, fb);
          if (task < NT_F) {
            tma_load2d(d + 32768, &maps.wu, nb * 128, k * 64, fb);
            tma_load2d(d + 40960, &maps.wu, nb * 128 + 64, k * 64, fb);
          }
        }
      }
    } else if (wp > 0) {
#pragma unroll 1
      while (true) {
        int blk = 0;
        if (lane == 0) blk = (int)atomicAdd(&gSync[SY_GQ], 1u);
        blk = __shfl_sync(~0u, blk, 0);
        if (blk >= S_LEN / 8) break;
        const int row = blk * 8 + (lane >> 2);
        const uint4* xr = reinterpret_cast<const uint4*>(x + (size_t)row * DM) + (lane & 3);
        const uint4* gr = reinterpret_cast<const uint4*>(gw) + (lane & 3);
        float g = 0.f;
#pragma unroll 2
        for (int i = 0; i < 32; i++) {
          const uint4 a = xr[i * 4], b = gr[i * 4];
          g += bf_lo(a.x) * bf_lo(b.x) + bf_hi(a.x) * bf_hi(b.x) + bf_lo(a.y) * bf_lo(b.y) + bf_hi(a.y) * bf_hi(b.y) +
               bf_lo(a.z) * bf_lo(b.z) + bf_hi(a.z) * bf_hi(b.z) + bf_lo(a.w) * bf_lo(b.w) + bf_hi(a.w) * bf_hi(b.w);
        }
        g += __shfl_xor_sync(~0u, g, 1); g += __shfl_xor_sync(~0u, g, 2);
        if ((lane & 3) == 0) gGate[row] = rcp(1.0f + ex2(g * -1.4426950408889634f));
        __threadfence();
        __syncwarp();
        if (lane == 0) asm volatile("red.release.gpu.global.add.u32 [%0], 1;" :: "l"(&gSync[SY_GATE]) : "memory");
      }
      asm volatile("griddepcontrol.wait;" ::: "memory");
      for (int i = blockIdx.x * 96 + (tid - 288); i < 2 * 64 * 32 * 16; i += gridDim.x * 96) gPart[i] = make_uint4(0, 0, 0, 0);
      for (int i = blockIdx.x * 96 + (tid - 288); i < NREP * 4 * 1024; i += gridDim.x * 96) gMem[i] = make_uint4(0, 0, 0, 0);
    }
  } else {
    asm volatile("setmaxnreg.inc.sync.aligned.u32 232;");
    int it = 0, nfin = 0;
    const int r = wg * 64 + wp * 16 + (lane & 7) + ((lane >> 3) & 1) * 8;
#pragma unroll 1
    for (int n = 0;; n++) {
      gwait(bars + 64 + 8 * (n & 1), (n >> 1) & 1);
      const int task = stask[n & 1];
      __syncwarp();
      if (lane == 0) mbar_arrive(bars + 80 + 8 * (n & 1));
      if (task >= NT_ALL) {
        break;
      }
      if (task < NT_F) {
        const int mb = task / 28, nb = task % 28;
        float acc[128];
        ZERO(acc, 128);
#pragma unroll 1
        for (int k = 0; k < DM / 64; k++, it++) {
          const int st = it % G_STAGES;
          gwait(bars + 8 * st, (it / G_STAGES) & 1);
          const uint32_t d16 = ((sb + st * G_STAGE) & 0x3FFFF) >> 4;
          WG_FENCE();
#pragma unroll
          for (int j = 0; j < 4; j++) wg_ss256<0, 1>(acc, mkd(d16 + wg * 512, j * 32, 0, 1024, 1), mkd(d16, 16384 + j * 2048, 8192, 1024, 1), 1);
          WG_COMMIT();
          if (k > 0) { WG_WAIT(1); if (lane == 0) mbar_arrive(bars + 32 + 8 * ((it - 1) % G_STAGES)); }
        }
        WG_WAIT(0);
        if (lane == 0) mbar_arrive(bars + 32 + 8 * ((it - 1) % G_STAGES));
#pragma unroll
        for (int j = 0; j < 8; j++) {
          uint32_t v[4];
#pragma unroll
          for (int q = 0; q < 4; q++) {
            const float g0 = acc[j * 8 + q * 2], g1 = acc[j * 8 + q * 2 + 1];
            const float u0 = acc[64 + j * 8 + q * 2], u1 = acc[64 + j * 8 + q * 2 + 1];
            v[q] = pack_bf16(g0 * rcp(1.0f + ex2(g0 * -1.4426950408889634f)) * u0, g1 * rcp(1.0f + ex2(g1 * -1.4426950408889634f)) * u1);
          }
          const int g = (j & 3) * 2 + (lane >> 4);
          stsm4(sOut + (j >> 2) * 16384 + r * 128 + ((g ^ (r & 7)) << 4), v[0], v[1], v[2], v[3]);
        }
        fence_async();
        bar_sync(1 + wg, 128);
        if ((tid & 127) == 0) {
          tma_store2d(&maps.hid_st, sOut + wg * 8192, nb * 128, mb * 128 + wg * 64);
          tma_store2d(&maps.hid_st, sOut + 16384 + wg * 8192, nb * 128 + 64, mb * 128 + wg * 64);
          bulk_commit();
          bulk_wait0();
          asm volatile("fence.proxy.async;" ::: "memory");
          asm volatile("red.release.gpu.global.add.u32 [%0], 1;" :: "l"(&gSync[SY_HID + mb]) : "memory");
        }
        bar_sync(1 + wg, 128);
      } else {
        const bool isA = task >= NT_F + NT_B;
        int tile = task - NT_F, part = 0, lg = 0;
        if (isA) decode_a(task - NT_F - NT_B, tile, part, lg);
        const int mb = tile >> 3, nb = tile & 7, nk = isA ? (HD / 64) >> lg : FF / 64, nparts = 1 << lg;
        const bool fin = isA && part + 1 == nparts;
        if (fin && (tid & 127) == 0) {
          asm volatile("fence.proxy.async;" ::: "memory");
          mbar_expect(bars + 96 + 8 * wg, 16384);
          tma_load2d(sOut + wg * 8192, &maps.b_st, nb * 128, mb * 128 + wg * 64, bars + 96 + 8 * wg);
          tma_load2d(sOut + 16384 + wg * 8192, &maps.b_st, nb * 128 + 64, mb * 128 + wg * 64, bars + 96 + 8 * wg);
        }
        __syncwarp();
        float acc[64];
        ZERO(acc, 64);
        if (tid == 0) TL(2048 + task);
#pragma unroll 1
        for (int k = 0; k < nk; k++, it++) {
          const int st = it % G_STAGES;
          gwait(bars + 8 * st, (it / G_STAGES) & 1);
          if (k == 0 && tid == 0) TL(3072 + task);
          const uint32_t d16 = ((sb + st * G_STAGE) & 0x3FFFF) >> 4;
          WG_FENCE();
#pragma unroll
          for (int j = 0; j < 4; j++) wg_ss128<0, 1>(acc, mkd(d16 + wg * 512, j * 32, 0, 1024, 1), mkd(d16, 16384 + j * 2048, 8192, 1024, 1), 1);
          WG_COMMIT();
          if (k > 0) { WG_WAIT(1); if (lane == 0) mbar_arrive(bars + 32 + 8 * ((it - 1) % G_STAGES)); }
        }
        if (tid == 0) TL(4096 + task);
        if (part + 1 < nparts) {
          WG_WAIT(0);
          if (lane == 0) mbar_arrive(bars + 32 + 8 * ((it - 1) % G_STAGES));
          float4* tp = gTail + (tile * 3 + part) * 4096 + tid;
#pragma unroll
          for (int j = 0; j < 16; j++) __stcg(tp + j * 256, make_float4(acc[j * 4], acc[j * 4 + 1], acc[j * 4 + 2], acc[j * 4 + 3]));
          __threadfence();
          __syncwarp();
          if (lane == 0) asm volatile("red.release.gpu.global.add.u32 [%0], 1;" :: "l"(&gSync[SY_T + tile]) : "memory");
          if (tid == 0) TL(5120 + task);
          continue;
        }
        float g0 = 0.f, g1 = 0.f;
        if (isA) {
          const int row = mb * 128 + wg * 64 + wp * 16 + (lane >> 2);
          g0 = __ldcg(&gGate[row]); g1 = __ldcg(&gGate[row + 8]);
          gwait(bars + 96 + 8 * wg, nfin & 1);
          nfin++;
        }
        WG_WAIT(0);
        if (lane == 0) mbar_arrive(bars + 32 + 8 * ((it - 1) % G_STAGES));
        if (nparts > 1) {
          if (lane == 0) wait_counter(&gSync[SY_T + tile], 8 * (nparts - 1));
          __syncwarp();
#pragma unroll 1
          for (int pp = 0; pp + 1 < nparts; pp++) {
            const float4* tp = gTail + (tile * 3 + pp) * 4096 + tid;
#pragma unroll
            for (int j = 0; j < 16; j++) {
              const float4 t = __ldcg(tp + j * 256);
              acc[j * 4] += t.x; acc[j * 4 + 1] += t.y; acc[j * 4 + 2] += t.z; acc[j * 4 + 3] += t.w;
            }
          }
        }
#pragma unroll
        for (int j = 0; j < 8; j++) {
          uint32_t v[4], bv[4];
          const uint32_t oa = sOut + (j >> 2) * 16384 + r * 128 + ((((j & 3) * 2 + (lane >> 4)) ^ (r & 7)) << 4);
          if (isA) ldsm4(bv, oa);
#pragma unroll
          for (int q = 0; q < 4; q++) {
            const int i = j * 8 + q * 2;
            if (isA) {
              const float g = (q & 1) ? g1 : g0;
              const uint32_t b = bv[q];
              v[q] = pack_bf16(g * acc[i] + (1.0f - g) * bf_lo(b), g * acc[i + 1] + (1.0f - g) * bf_hi(b));
            } else {
              v[q] = pack_bf16(acc[i], acc[i + 1]);
            }
          }
          stsm4(oa, v[0], v[1], v[2], v[3]);
        }
        fence_async();
        bar_sync(1 + wg, 128);
        if ((tid & 127) == 0) {
          const CUtensorMap* to = isA ? &maps.out : &maps.b_st;
          tma_store2d(to, sOut + wg * 8192, nb * 128, mb * 128 + wg * 64);
          tma_store2d(to, sOut + 16384 + wg * 8192, nb * 128 + 64, mb * 128 + wg * 64);
          bulk_commit();
          bulk_wait0();
          if (!isA) {
            asm volatile("fence.proxy.async;" ::: "memory");
            asm volatile("red.release.gpu.global.add.u32 [%0], 1;" :: "l"(&gSync[SY_B + tile]) : "memory");
          }
        }
        bar_sync(1 + wg, 128);
        if (tid == 0) TL(5120 + task);
      }
    }
  }
}

typedef CUresult (*EncodeFn)(CUtensorMap*, CUtensorMapDataType, cuuint32_t, void*, const cuuint64_t*, const cuuint64_t*,
                             const cuuint32_t*, const cuuint32_t*, CUtensorMapInterleave, CUtensorMapSwizzle,
                             CUtensorMapL2promotion, CUtensorMapFloatOOBfill);

void make_map(EncodeFn fn, CUtensorMap* m, const void* ptr, uint64_t inner, uint64_t outer, uint32_t bi, uint32_t bo,
              CUtensorMapSwizzle swz) {
  cuuint64_t dims[2] = {inner, outer};
  cuuint64_t strides[1] = {inner * 2};
  cuuint32_t box[2] = {bi, bo};
  cuuint32_t es[2] = {1, 1};
  fn(m, CU_TENSOR_MAP_DATA_TYPE_BFLOAT16, 2, const_cast<void*>(ptr), dims, strides, box, es, CU_TENSOR_MAP_INTERLEAVE_NONE, swz,
     CU_TENSOR_MAP_L2_PROMOTION_L2_256B, CU_TENSOR_MAP_FLOAT_OOB_FILL_NONE);
}

}

extern "C" void kernel_launch(void* const* d_in, const int* in_sizes, int n_in, void* d_out, int out_size) {
  (void)in_sizes; (void)n_in; (void)out_size;
  const __nv_bfloat16* x = (const __nv_bfloat16*)d_in[0];
  const __nv_bfloat16* mem0 = (const __nv_bfloat16*)d_in[1];
  const void* Wq = d_in[2]; const void* Wk = d_in[3]; const void* Wv = d_in[4]; const void* Wo = d_in[5];
  const void* Wg = d_in[8]; const void* Wu = d_in[9]; const void* Wd = d_in[10];
  const __nv_bfloat16* gw = (const __nv_bfloat16*)d_in[11];

  void* fnp = nullptr;
  cudaDriverEntryPointQueryResult qr;
  cudaGetDriverEntryPoint("cuTensorMapEncodeTiled", &fnp, cudaEnableDefault, &qr);
  EncodeFn fn = (EncodeFn)fnp;
  void *pOx, *pHid, *pB;
  cudaGetSymbolAddress(&pB, gB);
  cudaGetSymbolAddress(&pOx, gOx);
  cudaGetSymbolAddress(&pHid, gHid);

  const CUtensorMapSwizzle S128 = CU_TENSOR_MAP_SWIZZLE_128B, S64 = CU_TENSOR_MAP_SWIZZLE_64B;
  RecMaps rm;
  make_map(fn, &rm.w[0], Wq, HD, DM, 64, 64, S128);
  make_map(fn, &rm.w[1], Wk, HD, DM, 64, 64, S128);
  make_map(fn, &rm.w[2], Wv, HD, DM, 64, 64, S128);
  make_map(fn, &rm.wo, Wo, DM, HD, 64, 128, S128);
  make_map(fn, &rm.wo_half, Wo, DM, HD, 32, 64, S64);
  {
    cuuint64_t dims[3] = {64, (cuuint64_t)S_LEN, 16};
    cuuint64_t strides[2] = {DM * 2, 128};
    cuuint32_t box[3] = {64, 32, 2};
    cuuint32_t es[3] = {1, 1, 1};
    fn(&rm.x2, CU_TENSOR_MAP_DATA_TYPE_BFLOAT16, 3, (void*)x, dims, strides, box, es, CU_TENSOR_MAP_INTERLEAVE_NONE, S128,
       CU_TENSOR_MAP_L2_PROMOTION_L2_256B, CU_TENSOR_MAP_FLOAT_OOB_FILL_NONE);
    box[2] = 3;
    fn(&rm.x3, CU_TENSOR_MAP_DATA_TYPE_BFLOAT16, 3, (void*)x, dims, strides, box, es, CU_TENSOR_MAP_INTERLEAVE_NONE, S128,
       CU_TENSOR_MAP_L2_PROMOTION_L2_256B, CU_TENSOR_MAP_FLOAT_OOB_FILL_NONE);
    box[2] = 1;
    fn(&rm.x1, CU_TENSOR_MAP_DATA_TYPE_BFLOAT16, 3, (void*)x, dims, strides, box, es, CU_TENSOR_MAP_INTERLEAVE_NONE, S128,
       CU_TENSOR_MAP_L2_PROMOTION_L2_256B, CU_TENSOR_MAP_FLOAT_OOB_FILL_NONE);
  }
  make_map(fn, &rm.ox, pOx, HD, S_LEN, 64, 32, S128);
  GemmMaps gm;
  make_map(fn, &gm.x, x, DM, S_LEN, 64, 128, S128);
  make_map(fn, &gm.wg, Wg, FF, DM, 64, 64, S128);
  make_map(fn, &gm.wu, Wu, FF, DM, 64, 64, S128);
  make_map(fn, &gm.hid_st, pHid, FF, S_LEN, 64, 64, S128);
  make_map(fn, &gm.hid, pHid, FF, S_LEN, 64, 128, S128);
  make_map(fn, &gm.wd, Wd, DM, FF, 64, 64, S128);
  make_map(fn, &gm.b_st, pB, DM, S_LEN, 64, 64, S128);
  make_map(fn, &gm.ox, pOx, HD, S_LEN, 64, 128, S128);
  make_map(fn, &gm.wo, Wo, DM, HD, 64, 64, S128);
  make_map(fn, &gm.out, d_out, DM, S_LEN, 64, 64, S128);

  cudaFuncSetAttribute(rec_kernel, cudaFuncAttributeMaxDynamicSharedMemorySize, REC_SMEM + (REC_PROF ? 768 : 0));
  cudaFuncSetAttribute(gemm_kernel, cudaFuncAttributeMaxDynamicSharedMemorySize, G_SMEM);

  rec_kernel<<<dim3(3, 32), 384, REC_SMEM + (REC_PROF ? 768 : 0), cudaStreamPerThread>>>(rm, mem0, x);
  {
    cudaLaunchConfig_t cfg = {};
    cfg.gridDim = dim3(132); cfg.blockDim = dim3(384); cfg.dynamicSmemBytes = G_SMEM; cfg.stream = cudaStreamPerThread;
    cudaLaunchAttribute at[1];
    at[0].id = cudaLaunchAttributeProgrammaticStreamSerialization;
    at[0].val.programmaticStreamSerializationAllowed = 1;
    cfg.attrs = at; cfg.numAttrs = 1;
    cudaLaunchKernelEx(&cfg, gemm_kernel, gm, x, gw);
  }
}
```

```cpp
#include <cuda_runtime.h>
#include <cuda_bf16.h>
#include <cuda.h>
#include <stdint.h>

#define REC_PROF 0

namespace {

constexpr int S_LEN = 2048, DM = 1024, NH = 32, DH = 128, NMEM = 8, SEG = 32, NSEG = 64, FF = 3584;
constexpr int HD = NH * DH;

__device__ __nv_bfloat16 gOx[S_LEN * HD];
__device__ __nv_bfloat16 gHid[S_LEN * FF];
__device__ __nv_bfloat16 gB[S_LEN * DM];
__device__ float gGate[S_LEN];
__device__ float4 gTail[128 * 3 * 16 * 256];
enum { SY_QUEUE = 0, SY_GQ = 8, SY_GATE = 16, SY_HID = 32, SY_OX = 48, SY_B = 64, SY_T = 192, SY_N = 320 };
__device__ unsigned gSync[SY_N];
__device__ uint4 gPart[2 * 64 * 32 * 16];
#define NREP 2
__device__ uint4 gMem[NREP * 4 * 1024];

#define TL(i) do {} while (0)
__device__ __forceinline__ uint32_t smem_u32(const void* p) { return (uint32_t)__cvta_generic_to_shared(p); }
__device__ __forceinline__ uint32_t mapa(uint32_t a, uint32_t r) {
  uint32_t o; asm volatile("mapa.shared::cluster.u32 %0, %1, %2;" : "=r"(o) : "r"(a), "r"(r)); return o;
}
__device__ __forceinline__ void mbar_init(uint32_t bar, uint32_t cnt) {
  asm volatile("mbarrier.init.shared::cta.b64 [%0], %1;" :: "r"(bar), "r"(cnt) : "memory");
}
__device__ __forceinline__ void mbar_arrive(uint32_t bar) {
  asm volatile("mbarrier.arrive.shared::cta.b64 _, [%0];" :: "r"(bar) : "memory");
}
__device__ __forceinline__ void mbar_expect(uint32_t bar, uint32_t bytes) {
  asm volatile("mbarrier.arrive.expect_tx.shared::cta.b64 _, [%0], %1;" :: "r"(bar), "r"(bytes) : "memory");
}
__device__ __forceinline__ bool mbar_try(uint32_t bar, uint32_t parity) {
  uint32_t ok;
  asm volatile("{\n.reg .pred p;\nmbarrier.try_wait.parity.shared::cta.b64 p, [%1], %2;\nselp.u32 %0, 1, 0, p;\n}"
               : "=r"(ok) : "r"(bar), "r"(parity) : "memory");
  return ok != 0;
}
constexpr int SPIN_LIMIT = 1 << 15;
__device__ __forceinline__ void mbar_wait(uint32_t bar, uint32_t parity) {
#pragma unroll 1
  for (int i = 0; i < SPIN_LIMIT; i++) if (mbar_try(bar, parity)) break;
}
__device__ __forceinline__ void gwait(uint32_t bar, uint32_t parity) {
#pragma unroll 1
  for (int i = 0; i < (1 << 22); i++) if (mbar_try(bar, parity)) break;
}
__device__ __forceinline__ void fence_async() { asm volatile("fence.proxy.async.shared::cta;" ::: "memory"); }
__device__ __forceinline__ void bar_sync(int id, int n) { asm volatile("bar.sync %0, %1;" :: "r"(id), "r"(n) : "memory"); }
__device__ __forceinline__ void bar_arrive(int id, int n) { asm volatile("bar.arrive %0, %1;" :: "r"(id), "r"(n) : "memory"); }

__device__ __forceinline__ void tma_load2d(uint32_t dst, const CUtensorMap* tm, int c0, int c1, uint32_t bar) {
  asm volatile("cp.async.bulk.tensor.2d.shared::cluster.global.mbarrier::complete_tx::bytes [%0], [%1, {%3, %4}], [%2];"
               :: "r"(dst), "l"(tm), "r"(bar), "r"(c0), "r"(c1) : "memory");
}
__device__ __forceinline__ void tma_load3d_mc(uint32_t dst, const CUtensorMap* tm, int c0, int c1, int c2, uint32_t bar, uint16_t mask) {
  asm volatile("cp.async.bulk.tensor.3d.shared::cluster.global.mbarrier::complete_tx::bytes.multicast::cluster [%0], [%1, {%3, %4, %5}], [%2], %6;"
               :: "r"(dst), "l"(tm), "r"(bar), "r"(c0), "r"(c1), "r"(c2), "h"(mask) : "memory");
}
__device__ __forceinline__ void mbar_arrive_remote(uint32_t bar) {
  asm volatile("mbarrier.arrive.shared::cluster.b64 _, [%0];" :: "r"(bar) : "memory");
}
__device__ __forceinline__ uint32_t clk() { uint32_t t;
  asm volatile("mov.u32 %0, %%clock;" : "=r"(t) :: "memory")
; return t; }
__device__ __forceinline__ uint32_t phase_bad(const uint4& v, uint32_t ph) {
  uint32_t a, b;
  asm("lop3.b32 %0, %1, %2, %3, 0x7E;" : "=r"(a) : "r"(v.x), "r"(v.y), "r"(ph));
  asm("lop3.b32 %0, %1, %2, %3, 0x7E;" : "=r"(b) : "r"(v.z), "r"(v.w), "r"(ph));
  return (a | b) & 1u;
}
__device__ __forceinline__ bool has_zero(const uint4& v) { return min(min(v.x, v.y), min(v.z, v.w)) == 0; }
__device__ __forceinline__ uint32_t par(int s) { uint32_t r; asm volatile("and.b32 %0, %1, 1;" : "=r"(r) : "r"(s)); return r; }
__device__ __forceinline__ bool elect() {
  uint32_t p;
  asm volatile("{\n.reg .pred p;\nelect.sync _|p, 0xffffffff;\nselp.u32 %0, 1, 0, p;\n}" : "=r"(p));
  return p != 0;
}
__device__ __forceinline__ int rd_head() { int v; asm volatile("mov.u32 %0, %%ctaid.y;" : "=r"(v)); return v; }
__device__ __forceinline__ int rd_rank() { int v; asm volatile("mov.u32 %0, %%ctaid.x;" : "=r"(v)); return v; }
template <typename T> __device__ __forceinline__ void pin(T& v) {
  if constexpr (sizeof(T) == 8) asm volatile("" : "+l"(v)); else asm volatile("" : "+r"(v));
}
__device__ __forceinline__ int opaque(int t) { asm volatile("" : "+r"(t)); return t; }
#define otid() opaque(tid)
__device__ __forceinline__ float ex2(float x) { float y; asm("ex2.approx.ftz.f32 %0, %1;" : "=f"(y) : "f"(x)); return y; }
__device__ __forceinline__ float rcp(float x) { float y; asm("rcp.approx.ftz.f32 %0, %1;" : "=f"(y) : "f"(x)); return y; }
__device__ __forceinline__ void tma_prefetch2d(const CUtensorMap* tm, int c0, int c1) {
  asm volatile("cp.async.bulk.prefetch.tensor.2d.L2.global [%0, {%1, %2}];" :: "l"(tm), "r"(c0), "r"(c1) : "memory");
}
__device__ __forceinline__ void tma_store2d(const CUtensorMap* tm, uint32_t src, int c0, int c1) {
  asm volatile("cp.async.bulk.tensor.2d.global.shared::cta.bulk_group [%0, {%2, %3}], [%1];"
               :: "l"(tm), "r"(src), "r"(c0), "r"(c1) : "memory");
}
__device__ __forceinline__ void bulk_commit() { asm volatile("cp.async.bulk.commit_group;" ::: "memory"); }
__device__ __forceinline__ void bulk_wait_read0() { asm volatile("cp.async.bulk.wait_group.read 0;" ::: "memory"); }
__device__ __forceinline__ void bulk_wait0() { asm volatile("cp.async.bulk.wait_group 0;" ::: "memory"); }
__device__ __forceinline__ void bulk_s2c(uint32_t dst, uint32_t src, uint32_t bytes, uint32_t bar) {
  asm volatile("cp.async.bulk.shared::cluster.shared::cta.mbarrier::complete_tx::bytes [%0], [%1], %2, [%3];"
               :: "r"(dst), "r"(src), "r"(bytes), "r"(bar) : "memory");
}
__device__ __forceinline__ void st_async32(uint32_t dst, uint32_t v, uint32_t bar) {
  asm volatile("st.async.shared::cluster.mbarrier::complete_tx::bytes.u32 [%0], %1, [%2];" :: "r"(dst), "r"(v), "r"(bar) : "memory");
}
__device__ __forceinline__ void sts32(uint32_t a, uint32_t v) { asm volatile("st.shared.u32 [%0], %1;" :: "r"(a), "r"(v) : "memory"); }
__device__ __forceinline__ void sts128(uint32_t a, uint4 v) {
  asm volatile("st.shared.v4.u32 [%0], {%1,%2,%3,%4};" :: "r"(a), "r"(v.x), "r"(v.y), "r"(v.z), "r"(v.w) : "memory");
}
__device__ __forceinline__ uint4 ld_relaxed128(const void* p) {
  uint4 v;
  asm volatile("ld.relaxed.gpu.global.v4.u32 {%0,%1,%2,%3}, [%4];" : "=r"(v.x), "=r"(v.y), "=r"(v.z), "=r"(v.w) : "l"(p) : "memory");
  return v;
}
__device__ __forceinline__ void st_relaxed128(void* p, uint32_t a, uint32_t b, uint32_t c, uint32_t d) {
  asm volatile("st.relaxed.gpu.global.v4.u32 [%0], {%1,%2,%3,%4};" :: "l"(p), "r"(a), "r"(b), "r"(c), "r"(d) : "memory");
}
__device__ __forceinline__ void st_relaxed64(void* p, uint32_t a, uint32_t b) {
  asm volatile("st.relaxed.gpu.global.v2.u32 [%0], {%1,%2};" :: "l"(p), "r"(a), "r"(b) : "memory");
}
__device__ __forceinline__ uint32_t nz(uint32_t w) { return w == 0 ? 0x80000000u : w; }
__device__ __forceinline__ float bf_lo(uint32_t w) { return __uint_as_float(w << 16); }
__device__ __forceinline__ float bf_hi(uint32_t w) { return __uint_as_float(w & 0xFFFF0000u); }
__device__ __forceinline__ void st_relaxed32(void* p, uint32_t a) {
  asm volatile("st.relaxed.gpu.global.u32 [%0], %1;" :: "l"(p), "r"(a) : "memory");
}
__device__ __forceinline__ uint32_t pack_bf16(float lo, float hi) {
  uint32_t r; asm("cvt.rn.bf16x2.f32 %0, %1, %2;" : "=r"(r) : "f"(hi), "f"(lo)); return r;
}
__device__ __forceinline__ void ldsm4_t(uint32_t* r, uint32_t addr) {
  asm volatile("ldmatrix.sync.aligned.m8n8.x4.trans.shared.b16 {%0,%1,%2,%3}, [%4];"
               : "=r"(r[0]), "=r"(r[1]), "=r"(r[2]), "=r"(r[3]) : "r"(addr) : "memory");
}
__device__ __forceinline__ void ldsm4(uint32_t* r, uint32_t addr) {
  asm volatile("ldmatrix.sync.aligned.m8n8.x4.shared.b16 {%0,%1,%2,%3}, [%4];"
               : "=r"(r[0]), "=r"(r[1]), "=r"(r[2]), "=r"(r[3]) : "r"(addr) : "memory");
}
__device__ __forceinline__ void mma16816(float* d, const uint32_t* a, uint32_t b0, uint32_t b1) {
  asm volatile("mma.sync.aligned.m16n8k16.row.col.f32.bf16.bf16.f32 {%0,%1,%2,%3}, {%4,%5,%6,%7}, {%8,%9}, {%0,%1,%2,%3};"
               : "+f"(d[0]), "+f"(d[1]), "+f"(d[2]), "+f"(d[3]) : "r"(a[0]), "r"(a[1]), "r"(a[2]), "r"(a[3]), "r"(b0), "r"(b1));
}
__device__ __forceinline__ void mma1688(float* d, uint32_t a0, uint32_t a1, uint32_t b0) {
  asm volatile("mma.sync.aligned.m16n8k8.row.col.f32.bf16.bf16.f32 {%0,%1,%2,%3}, {%4,%5}, {%6}, {%0,%1,%2,%3};"
               : "+f"(d[0]), "+f"(d[1]), "+f"(d[2]), "+f"(d[3]) : "r"(a0), "r"(a1), "r"(b0));
}
__device__ __forceinline__ void lds128(uint32_t* r, uint32_t addr) {
  asm volatile("ld.shared.v4.u32 {%0,%1,%2,%3}, [%4];" : "=r"(r[0]), "=r"(r[1]), "=r"(r[2]), "=r"(r[3]) : "r"(addr) : "memory");
}
__device__ __forceinline__ void stsm4_t(uint32_t addr, uint32_t a, uint32_t b, uint32_t c, uint32_t d) {
  asm volatile("stmatrix.sync.aligned.m8n8.x4.trans.shared.b16 [%0], {%1,%2,%3,%4};" :: "r"(addr), "r"(a), "r"(b), "r"(c), "r"(d) : "memory");
}
__device__ __forceinline__ void stsm4(uint32_t addr, uint32_t a, uint32_t b, uint32_t c, uint32_t d) {
  asm volatile("stmatrix.sync.aligned.m8n8.x4.shared.b16 [%0], {%1,%2,%3,%4};" :: "r"(addr), "r"(a), "r"(b), "r"(c), "r"(d) : "memory");
}
__device__ __forceinline__ uint32_t movm_t(uint32_t a) {
  uint32_t d; asm volatile("movmatrix.sync.aligned.m8n8.trans.b16 %0, %1;" : "=r"(d) : "r"(a)); return d;
}

struct Desc { uint32_t base, off, hi; };
__device__ __forceinline__ Desc mkd(uint32_t base, uint32_t boff, uint32_t lbo, uint32_t sbo, uint32_t swz) {
  return Desc{base, (boff >> 4) + ((lbo >> 4) << 16), (sbo >> 4) | (swz << 30)};
}
#define WG_FENCE() asm volatile("wgmma.fence.sync.aligned;" ::: "memory")
#define WG_COMMIT() asm volatile("wgmma.commit_group.sync.aligned;" ::: "memory")
#define WG_WAIT(n) asm volatile("wgmma.wait_group.sync.aligned " #n ";" ::: "memory")

#define ZERO(a, n) _Pragma("unroll") for (int _i = 0; _i < n; _i++) a[_i] = 0.f
#define F4(d, o) "+f"(d[o]), "+f"(d[o + 1]), "+f"(d[o + 2]), "+f"(d[o + 3])
#define F16(d, o) F4(d, o), F4(d, o + 4), F4(d, o + 8), F4(d, o + 12)
#define F64(d, o) F16(d, o), F16(d, o + 16), F16(d, o + 32), F16(d, o + 48)

template <int TB> __device__ __forceinline__ void wg_rs8(float* d, const uint32_t* a, Desc b, int sc) {
  asm volatile("{\n.reg .pred p;\n.reg .b32 lb;\n.reg .b64 db;\nsetp.ne.b32 p, %11, 0;\nadd.u32 lb, %8, %9;\nmov.b64 db, {lb, %10};\n"
               "wgmma.mma_async.sync.aligned.m64n8k16.f32.bf16.bf16 {%0,%1,%2,%3}, {%4,%5,%6,%7}, db, p, 1, 1, %12;\n}"
               : F4(d, 0) : "r"(a[0]), "r"(a[1]), "r"(a[2]), "r"(a[3]), "r"(b.base), "r"(b.off), "r"(b.hi), "r"(sc), "n"(TB));
}
template <int TA, int TB> __device__ __forceinline__ void wg_ss8(float* d, Desc a, Desc b, int sc) {
  asm volatile("{\n.reg .pred p;\n.reg .b32 la, lb;\n.reg .b64 da, db;\nsetp.ne.b32 p, %10, 0;\n"
               "add.u32 la, %4, %5;\nmov.b64 da, {la, %6};\nadd.u32 lb, %7, %8;\nmov.b64 db, {lb, %9};\n"
               "wgmma.mma_async.sync.aligned.m64n8k16.f32.bf16.bf16 {%0,%1,%2,%3}, da, db, p, 1, 1, %11, %12;\n}"
               : F4(d, 0) : "r"(a.base), "r"(a.off), "r"(a.hi), "r"(b.base), "r"(b.off), "r"(b.hi), "r"(sc), "n"(TA), "n"(TB));
}
template <int TB> __device__ __forceinline__ void wg_rs32(float* d, const uint32_t* a, Desc b, int sc) {
  asm volatile("{\n.reg .pred p;\n.reg .b32 lb;\n.reg .b64 db;\nsetp.ne.b32 p, %23, 0;\nadd.u32 lb, %20, %21;\nmov.b64 db, {lb, %22};\n"
               "wgmma.mma_async.sync.aligned.m64n32k16.f32.bf16.bf16 {%0,%1,%2,%3,%4,%5,%6,%7,%8,%9,%10,%11,%12,%13,%14,%15}, {%16,%17,%18,%19}, db, p, 1, 1, %24;\n}"
               : F16(d, 0) : "r"(a[0]), "r"(a[1]), "r"(a[2]), "r"(a[3]), "r"(b.base), "r"(b.off), "r"(b.hi), "r"(sc), "n"(TB));
}
template <int TA, int TB> __device__ __forceinline__ void wg_ss32(float* d, Desc a, Desc b, int sc) {
  asm volatile("{\n.reg .pred p;\n.reg .b32 la, lb;\n.reg .b64 da, db;\nsetp.ne.b32 p, %22, 0;\n"
               "add.u32 la, %16, %17;\nmov.b64 da, {la, %18};\nadd.u32 lb, %19, %20;\nmov.b64 db, {lb, %21};\n"
               "wgmma.mma_async.sync.aligned.m64n32k16.f32.bf16.bf16 {%0,%1,%2,%3,%4,%5,%6,%7,%8,%9,%10,%11,%12,%13,%14,%15}, da, db, p, 1, 1, %23, %24;\n}"
               : F16(d, 0) : "r"(a.base), "r"(a.off), "r"(a.hi), "r"(b.base), "r"(b.off), "r"(b.hi), "r"(sc), "n"(TA), "n"(TB));
}
template <int TA, int TB> __device__ __forceinline__ void wg_ss40(float* d, Desc a, Desc b, int sc) {
  asm volatile("{\n.reg .pred p;\n.reg .b32 la, lb;\n.reg .b64 da, db;\nsetp.ne.b32 p, %26, 0;\n"
               "add.u32 la, %20, %21;\nmov.b64 da, {la, %22};\nadd.u32 lb, %23, %24;\nmov.b64 db, {lb, %25};\n"
               "wgmma.mma_async.sync.aligned.m64n40k16.f32.bf16.bf16 {%0,%1,%2,%3,%4,%5,%6,%7,%8,%9,%10,%11,%12,%13,%14,%15,%16,%17,%18,%19}, da, db, p, 1, 1, %27, %28;\n}"
               : F16(d, 0), F4(d, 16) : "r"(a.base), "r"(a.off), "r"(a.hi), "r"(b.base), "r"(b.off), "r"(b.hi), "r"(sc), "n"(TA), "n"(TB));
}
template <int TA, int TB> __device__ __forceinline__ void wg_ss128(float* d, Desc a, Desc b, int sc) {
  asm volatile("{\n.reg .pred p;\n.reg .b32 la, lb;\n.reg .b64 da, db;\nsetp.ne.b32 p, %70, 0;\n"
               "add.u32 la, %64, %65;\nmov.b64 da, {la, %66};\nadd.u32 lb, %67, %68;\nmov.b64 db, {lb, %69};\n"
               "wgmma.mma_async.sync.aligned.m64n128k16.f32.bf16.bf16 {%0,%1,%2,%3,%4,%5,%6,%7,%8,%9,%10,%11,%12,%13,%14,%15,%16,%17,%18,%19,%20,%21,%22,%23,%24,%25,%26,%27,%28,%29,%30,%31,%32,%33,%34,%35,%36,%37,%38,%39,%40,%41,%42,%43,%44,%45,%46,%47,%48,%49,%50,%51,%52,%53,%54,%55,%56,%57,%58,%59,%60,%61,%62,%63}, da, db, p, 1, 1, %71, %72;\n}"
               : F64(d, 0) : "r"(a.base), "r"(a.off), "r"(a.hi), "r"(b.base), "r"(b.off), "r"(b.hi), "r"(sc), "n"(TA), "n"(TB));
}
template <int TA, int TB> __device__ __forceinline__ void wg_ss256(float* d, Desc a, Desc b, int sc) {
  asm volatile("{\n.reg .pred p;\n.reg .b32 la, lb;\n.reg .b64 da, db;\nsetp.ne.b32 p, %134, 0;\n"
               "add.u32 la, %128, %129;\nmov.b64 da, {la, %130};\nadd.u32 lb, %131, %132;\nmov.b64 db, {lb, %133};\n"
               "wgmma.mma_async.sync.aligned.m64n256k16.f32.bf16.bf16 {%0,%1,%2,%3,%4,%5,%6,%7,%8,%9,%10,%11,%12,%13,%14,%15,%16,%17,%18,%19,%20,%21,%22,%23,%24,%25,%26,%27,%28,%29,%30,%31,%32,%33,%34,%35,%36,%37,%38,%39,%40,%41,%42,%43,%44,%45,%46,%47,%48,%49,%50,%51,%52,%53,%54,%55,%56,%57,%58,%59,%60,%61,%62,%63,%64,%65,%66,%67,%68,%69,%70,%71,%72,%73,%74,%75,%76,%77,%78,%79,%80,%81,%82,%83,%84,%85,%86,%87,%88,%89,%90,%91,%92,%93,%94,%95,%96,%97,%98,%99,%100,%101,%102,%103,%104,%105,%106,%107,%108,%109,%110,%111,%112,%113,%114,%115,%116,%117,%118,%119,%120,%121,%122,%123,%124,%125,%126,%127}, da, db, p, 1, 1, %135, %136;\n}"
               : F64(d, 0), F64(d, 64) : "r"(a.base), "r"(a.off), "r"(a.hi), "r"(b.base), "r"(b.off), "r"(b.hi), "r"(sc), "n"(TA), "n"(TB));
}

constexpr int NRSC = 11;
#define GCH 9
#define KV_EARLY 0
#define QCH 2
#define NUE 2
__host__ __device__ constexpr int rs_chunk(int i) { return i == 0 ? 0 : i + NUE; }
__host__ __device__ constexpr int u_chunk(int i) { return i < NUE ? i + 1 : i + 7; }
__host__ __device__ constexpr bool is_u(int ch) { return (ch >= 1 && ch <= NUE) || ch >= 7 + NUE; }
__host__ __device__ constexpr int cls_idx(int ch) { return is_u(ch) ? (ch <= NUE ? ch - 1 : ch - 7) : (ch == 0 ? 0 : ch - NUE); }
constexpr uint32_t R_SS = 0;
constexpr uint32_t R_POOL = 81920;
constexpr uint32_t R_MRS = R_POOL + 25600;
constexpr uint32_t R_V = 118784;
constexpr uint32_t R_K = 129024;
constexpr uint32_t R_Q = 139264;
constexpr uint32_t R_WO = R_Q + 10240;
constexpr uint32_t R_W4 = R_WO + 65536;
constexpr uint32_t R_P0 = R_K + 8192;
constexpr uint32_t R_PX = R_Q + 5120;
constexpr uint32_t R_BAR = 231424;
constexpr uint32_t R_INV = R_BAR + 224;
constexpr uint32_t REC_SMEM = 231680;
enum { B_XFULL = 0, B_SSFULL = 4, B_XDONE = 5, B_PRO = 6, B_SDONE = 7, B_POOL = 8, B_QKV = 9, B_KVX = 10, B_TFREE = 11, B_WSS = 12, B_WO = 13, B_W0 = 14, B_XTILE = 17, B_PUB = 18, B_VX = 19, B_LPUB = 20 };
#define SS_ISSUE 0

struct RecMaps { CUtensorMap w[3]; CUtensorMap wo; CUtensorMap wo_half; CUtensorMap x3; CUtensorMap x2; CUtensorMap x1; CUtensorMap ox; int tune[8]; };

#define PROF(i) do {} while (0)
#define PDUMP() do {} while (0)
#define PVAL(i, v) do {} while (0)
#define PSYNC() do {} while (0)
__device__ constexpr int kDelay[8] = {220, 220, 0, 1000, 0, 0, 0, 0};
#define DELAY(i) do { if (kDelay[i] > 0) { unsigned _t0 = clock(); while ((int)(clock() - _t0) < kDelay[i]) {} } } while (0)

__global__ void __cluster_dims__(3, 1, 1) __launch_bounds__(384, 1)
rec_kernel(const __grid_constant__ RecMaps maps, const __nv_bfloat16* __restrict__ mem0, const __nv_bfloat16* __restrict__ xg,
           const __nv_bfloat16* __restrict__ wog) {
  extern __shared__ __align__(1024) uint8_t smem[];
  const uint32_t sb = smem_u32(smem);
  const int tid = opaque(threadIdx.x);
  const int wid = __shfl_sync(~0u, tid >> 5, 0), wg = wid >> 2, wp = wid & 3;
  const uint32_t s16 = (sb & 0x3FFFF) >> 4;
  const int h = blockIdx.y, c = blockIdx.x;
  const uint32_t bars = sb + R_BAR;
  auto BAR = [&](int i) { return bars + 8u * i; };
  const uint32_t sWo = sb + R_WO;

  if (tid == 0 && h == 0 && c == 0) TL(0);
  if (tid == 0) {
    for (int i = 0; i < 5; i++) mbar_init(BAR(B_XFULL + i), 1);
    mbar_init(BAR(B_XDONE), 24); mbar_init(BAR(B_XTILE), 24); mbar_init(BAR(B_PUB), 8); mbar_init(BAR(B_LPUB), 4); mbar_init(BAR(B_VX), c == 2 ? 9 : 1); mbar_init(BAR(B_PRO), 24); mbar_init(BAR(B_SDONE), 2); mbar_init(BAR(B_POOL), 3);
    mbar_init(BAR(B_QKV), c == 2 ? 1 : 9); mbar_init(BAR(B_KVX), 1); mbar_init(BAR(B_TFREE), c == 0 ? 1 : 2);
    mbar_init(BAR(B_WSS), 1); mbar_init(BAR(B_WO), 1);
    for (int i = 0; i < 3; i++) mbar_init(BAR(B_W0 + i), 1);
    asm volatile("fence.mbarrier_init.release.cluster;" ::: "memory");
    fence_async();
    mbar_expect(BAR(B_W0 + 0), 81920); mbar_expect(BAR(B_W0 + 1), 32768); mbar_expect(BAR(B_W0 + 2), 65536);
  }
  if (h == 0 && c == 0 && tid < SY_N) { gSync[tid] = 0; __threadfence(); }
  __syncthreads();
  asm volatile("barrier.cluster.arrive.relaxed.aligned;" ::: "memory");
  asm volatile("griddepcontrol.launch_dependents;" ::: "memory");
  if ((tid & 31) == 0) {
    if (wid < NRSC) {
      const int i = wid;
      const int ch = i < 7 ? rs_chunk(i) : u_chunk(i - 7);
      const uint32_t dst = i < 5 ? sb + R_SS + i * 16384 : (i < 7 ? sb + R_POOL + (i - 5) * 16384 : sWo + (i - 7) * 8192);
      const uint32_t bar = BAR(B_W0 + (i < 5 ? 0 : (i < 7 ? 1 : 2)));
      tma_load2d(dst, &maps.w[c], h * 128, ch * 64, bar);
      tma_load2d(dst + (i < 7 ? 8192 : 32768), &maps.w[c], h * 128 + 64, ch * 64, bar);
    } else if (h * 3 + c < 8) {
      asm volatile("cp.async.bulk.prefetch.L2.global [%0], %1;" :: "l"(reinterpret_cast<const char*>(xg) + (h * 3 + c) * 32768), "r"(32768) : "memory");
    }
  }
  __syncwarp();
  asm volatile("barrier.cluster.wait.aligned;" ::: "memory");

  { constexpr int ROLE = 0; PROF(15); (void)ROLE; }

  const float sl2e = 0.08838834764831845f * 1.4426950408889634f;
  if (wg < 2) {
    asm volatile("setmaxnreg.inc.sync.aligned.u32 224;");
    constexpr int ROLE = 0; (void)ROLE;
    uint32_t wa[28 * 4], wo[16 * 4];
#pragma unroll
    for (int i = 0; i < 64; i++) wo[i] = 0;
    {
      const uint32_t fo = (((tid >> 4) & 1) * 8 + (tid & 7)) * 128 + (((wp * 2 + ((tid >> 3) & 1)) ^ (tid & 7)) << 4);
#pragma unroll
      for (int i = 0; i < 7; i++) {
        if (i % 5 == 0) mbar_wait(BAR(B_W0 + i / 5), 0);
        if (i == 0 && tid == 0 && h == 0 && c == 0) TL(5);
        const uint32_t src = (i < 5 ? sb + R_SS + i * 16384 : sb + R_POOL + (i - 5) * 16384) + wg * 8192 + fo;
#pragma unroll
        for (int j = 0; j < 4; j++) ldsm4_t(&wa[(i * 4 + j) * 4], src + j * 2048);
        if (i == 4) {
          bar_sync(3, 256);
          if (tid == 0) { fence_async(); mbar_expect(BAR(B_WSS), 81920); }
          if ((tid & 31) == 0 && wid >= 1 && wid < 6) {
            fence_async();
            for (int t = 0; t < 2; t++)
              tma_load2d(sb + R_SS + t * 40960 + (wid - 1) * 8192, &maps.w[c], h * 128 + t * 64, (NRSC + wid - 1) * 64, BAR(B_WSS));
          }
          __syncwarp();
        }
      }
      bar_sync(3, 256);
      if (tid == 0) {
        fence_async();
        mbar_arrive_remote(mapa(BAR(B_POOL), 0));
        mbar_expect(BAR(B_WO), c == 0 ? 16384 : 24576);
        tma_load2d(sb + R_W4, &maps.wo, (12 + c) * 64, h * 128, BAR(B_WO));
        if (c != 0) {
          tma_load2d(sb + R_Q, &maps.wo_half, 928 + c * 32, h * 128, BAR(B_WO));
          tma_load2d(sb + R_Q + 5120, &maps.wo_half, 928 + c * 32, h * 128 + 64, BAR(B_WO));
        }
      } else if (tid == 32) {
        for (int t = 0; t < 4; t++) tma_prefetch2d(&maps.wo, ((t >> 1) * 6 + c * 2 + (t & 1)) * 64, h * 128);
      } else if (tid == 64) {
        const uint32_t per = 40960;
        asm volatile("cp.async.bulk.prefetch.L2.global [%0], %1;" :: "l"(reinterpret_cast<const char*>(xg) + 262144 + (h * 3 + c) * per), "r"(per) : "memory");
      }
      __syncwarp();
    }
    mbar_wait(BAR(B_WSS), 0);
    mbar_wait(BAR(B_W0 + 2), 0);
    if (tid == 0 && h == 0 && c == 0) TL(6);
    const uint32_t aSS = s16 + (R_SS >> 4) + wg * 2560;
    const uint32_t aU = s16 + (R_WO >> 4) + wg * 2048;
#define TBASE (R_Q - rd_rank() * 10240)
    PROF(0);
    if (tid == 0 && h == 0 && c == 0) TL(1);
    if (tid == 4) mbar_expect(BAR(B_SSFULL), 20480);
    __syncwarp();
    uint32_t ma = 0;

#pragma unroll 1
    for (int s = -1; s < NSEG; s++) {
      float mr[4];
      ZERO(mr, 4);
      if (s >= 0) {
        float am[12];
        ZERO(am, 12);
        uint32_t bf[4][4];
#pragma unroll
        for (int j = 0; j < 3; j++) ldsm4(bf[j], (ma ^ ((j & 1) << 6)) + rs_chunk(j >> 1) * 1024);
#pragma unroll
        for (int j = 0; j < 14; j++) {
          if (j + 3 < 14) ldsm4(bf[(j + 3) & 3], (ma ^ (((j + 3) & 1) << 6)) + rs_chunk((j + 3) >> 1) * 1024);
          mma16816((j & 1) ? am + 4 : mr, &wa[j * 8], bf[j & 3][0], bf[j & 3][1]);
          mma16816((j & 1) ? am + 8 : am, &wa[j * 8 + 4], bf[j & 3][2], bf[j & 3][3]);
        }
#pragma unroll
        for (int e = 0; e < 4; e++) mr[e] = (mr[e] + am[e]) + (am[4 + e] + am[8 + e]);
        PROF(8);
      }
      PROF(1);
      float a40[20];
      ZERO(a40, 16);
#pragma unroll
      for (int e = 0; e < 4; e++) a40[16 + e] = mr[e];
      float au[4];
      ZERO(au, 4);
      WG_FENCE();
#pragma unroll
      for (int j = 0; j < 16; j++)
        wg_ss8<1, 0>(au, mkd(aU, j * 2048, 0, 1024, 1), mkd(s16, R_MRS + u_chunk(j >> 2) * 1024 + (j & 3) * 32, 0, 1024, 1), 1);
      WG_COMMIT();
      if (s + 1 < NSEG) mbar_wait(BAR(B_SSFULL), (s + 1) & 1);
      WG_FENCE();
#pragma unroll
      for (int j = 0; j < 20; j++)
        wg_ss40<1, 0>(a40, mkd(aSS, j * 2048, 0, 1024, 1), mkd(s16, R_POOL + (j >> 2) * 5120 + (j & 3) * 32, 0, 1024, 1), 1);
      WG_COMMIT();
      uint32_t o0, o1, o2, rb0, rb1, rb2;
      {
        const int ln = otid() & 31, tok = ln >> 2, rk = rd_rank();
        o0 = sb + R_Q - rk * 10240 + wg * 5120 + 4096 + tok * 128 + (((wp * 2) ^ tok) << 4) + (ln & 3) * 4;
        const uint32_t r1 = rk == 2 ? 0 : rk + 1, r2 = rk == 0 ? 2 : rk - 1;
        rb0 = rk == 2 ? BAR(B_VX) : BAR(B_QKV);
        o1 = mapa(o0, r1); o2 = mapa(o0, r2); rb1 = mapa(rb0, r1); rb2 = mapa(rb0, r2);
      }
      WG_WAIT(0);
      float ax[16];
#pragma unroll
      for (int e = 0; e < 16; e++) ax[e] = a40[e];
      if (s >= 0) {
        PROF(2);
        const uint32_t m0 = movm_t(pack_bf16(a40[16] + au[0], a40[17] + au[1]));
        const uint32_t m1 = movm_t(pack_bf16(a40[18] + au[2], a40[19] + au[3]));
        st_async32(o1, m0, rb1);
        st_async32(o2, m0, rb2);
        st_async32(o1 ^ 16, m1, rb1);
        st_async32(o2 ^ 16, m1, rb2);
        sts32(o0, m0);
        sts32(o0 ^ 16, m1);
        __syncwarp();
        if (elect()) mbar_arrive(rb0);
      }
      if (s + 1 < NSEG && elect()) mbar_arrive_remote(mapa(BAR(B_PRO), 0));
      if (s == NSEG - 1) break;
      if (tid < 5 && (tid < 4 || s + 2 < NSEG)) mbar_expect(BAR(B_XFULL + tid), tid < 3 ? 12288 : (tid == 3 ? 8192 : 20480));
      if (c == 0 && tid == 224) {
        mbar_wait(BAR(B_PRO), (s + 1) & 1);
        for (int j = 0; j < 3; j++) tma_load3d_mc(sb + R_POOL + j * 12288, &maps.x3, 0, (s + 1) * SEG, j * 3, BAR(B_XFULL + j), 7);
      }
      __syncwarp();
      if (s <= 0) {
        const int t = otid();
        const uint2* wp0 = reinterpret_cast<const uint2*>(wog + (size_t)(rd_head() * 128 + ((t & 31) >> 2)) * DM + (rd_rank() * 2 + wg) * 64 + wp * 16) + (t & 3);
        if (s < 0) {
#pragma unroll
          for (int i = 0; i < 16; i++) { const uint2 u = __ldg(wp0 + i * 8 * (DM / 4)); wo[2 * i] = u.x; wo[2 * i + 1] = u.y; }
        } else {
#pragma unroll
          for (int i = 0; i < 16; i++) { const uint2 u = __ldg(wp0 + i * 8 * (DM / 4) + 96); wo[32 + 2 * i] = u.x; wo[33 + 2 * i] = u.y; }
#pragma unroll
          for (int i = 0; i < 64; i++) wo[i] = movm_t(wo[i]);
        }
      }
      if (s >= 0) {
        PROF(3);
        PDUMP();
        const int ln = otid() & 31;
        uint32_t pdst = (((s & 1) * 64 + rd_rank() * 8 + wg * 4 + wp) * 32 + rd_head()) * 256 + ((ln & 3) * 8 + (ln >> 2)) * 8;
        uint32_t oa = sb + R_Q + 4096 + ln * 16;
        pin(pdst); pin(oa);
        if (wid == 6) {
          bar_sync(5, 160);
          const int rk = rd_rank();
          if (tid == 192 && rk != 0) tma_load3d_mc(sb + R_K, &maps.x2, 0, (s + 1) * SEG, 9, BAR(B_XFULL + 3), (uint16_t)(1 << rk));
          __syncwarp();
        }
        bar_sync(7, 384);
        uint32_t ob[2][4];
        lds128(ob[0], oa);
        lds128(ob[1], oa + 512);
        float a0[4], a1[4];
        ZERO(a0, 4); ZERO(a1, 4);
#pragma unroll
        for (int i = 0; i < 4; i++) {
          mma16816(a0, &wo[i * 8], ob[i & 1][0], ob[i & 1][1]);
          mma16816(a1, &wo[32 + i * 8], ob[i & 1][0], ob[i & 1][1]);
          mma16816(a0, &wo[i * 8 + 4], ob[i & 1][2], ob[i & 1][3]);
          mma16816(a1, &wo[32 + i * 8 + 4], ob[i & 1][2], ob[i & 1][3]);
          if (i < 2) lds128(ob[i & 1], oa + 5120 + i * 512);
        }
        char* pd = reinterpret_cast<char*>(gPart) + pdst;
        st_relaxed64(pd, nz(pack_bf16(a0[0], a0[1])), nz(pack_bf16(a0[2], a0[3])));
        st_relaxed64(pd + 24 * 8192, nz(pack_bf16(a1[0], a1[1])), nz(pack_bf16(a1[2], a1[3])));
        PROF(4);
        mbar_wait(BAR(B_XFULL), (s + 1) & 1);
        bar_sync(9, 384);
        PROF(5);
        DELAY(4);
      }
      uint4 v[4];
      const uint4* src = gMem + ((rd_head() & (NREP - 1)) * 4 + ((s + 1) & 3)) * 1024 + otid();
#pragma unroll
      for (int ch = 0; ch < NRSC; ch++) {
        if (ch % 3 == 0 && (ch > 0 || s < 0)) mbar_wait(BAR(B_XFULL + ch / 3), (s + 1) & 1);
        if (ch == 0) { PROF(13); } else if (ch == 9) { PROF(14); }
        if (ch == 7 + NUE) {
          if (tid == 224 && s + 2 < NSEG && rd_rank() == 1) {
            mbar_wait(BAR(B_XTILE), (s + 1) & 1);
            DELAY(5);
            for (int j = 0; j < 5; j++) tma_load3d_mc(sb + R_POOL + j * 5120, &maps.x1, 0, (s + 2) * SEG, NRSC + j, BAR(B_SSFULL), 7);
          }
          __syncwarp();
          if (s >= 0 && rd_rank() != 0) mbar_wait(BAR(B_LPUB), s & 1);
        }
        if (ch % 3 == 0 || ch == 7 + NUE || ch == GCH + 1 || ch == 7) WG_FENCE();
#pragma unroll
        for (int j = 0; j < 4; j++)
        {
          const Desc db = mkd(s16, (ch < 9 ? R_POOL + ch * 4096 : R_K + (ch - 9) * 4096) + j * 32, 0, 1024, 1);
          if (is_u(ch)) wg_ss32<1, 0>(ax, mkd(aU, (cls_idx(ch) * 4 + j) * 2048, 0, 1024, 1), db, 1);
          else wg_rs32<0>(ax, &wa[(cls_idx(ch) * 4 + j) * 4], db, 1);
        }
        if (ch % 3 == 2 || ch == 10 || ch == 6 + NUE || ch == GCH || ch == 6) WG_COMMIT();
        if (ch == 6) {
          WG_WAIT(1);
          if (elect()) mbar_arrive_remote(mapa(BAR(B_XTILE), 1));
        }
        if (ch == GCH) {
          if (s >= 0) {
            mbar_wait(BAR(B_PUB), s & 1);
            DELAY(1);
            PROF(10);
#pragma unroll
            for (int i = 0; i < 4; i++) v[i] = ld_relaxed128(src + i * 256);
          } else {
            const int t = otid(), n = (t >> 3) & 7;
#pragma unroll
            for (int i = 0; i < 4; i++) v[i] = *reinterpret_cast<const uint4*>(mem0 + n * DM + (i * 4 + (t >> 6)) * 64 + ((t & 7) ^ n) * 8);
          }
        }
      }
      WG_WAIT(0);
      { const int ln = otid() & 31; if (ln < 3) mbar_arrive_remote(mapa(BAR(B_XDONE), ln)); }
      PROF(6);
      if (s >= 0 && rd_rank() == 0) mbar_wait(BAR(B_TFREE), s & 1);
      bar_sync(3, 256);
      {
        const int ln = otid() & 31, r = ln & 7, blk = ln >> 3;
        const uint32_t ta = sb + TBASE + wg * 5120 + ((blk >> 1) * 8 + r) * 128 + (((wp * 2 + (blk & 1)) ^ r) << 4);
#pragma unroll
        for (int jj = 0; jj < 2; jj++)
          stsm4_t(ta + jj * 2048, pack_bf16(ax[jj * 8 + 0], ax[jj * 8 + 1]), pack_bf16(ax[jj * 8 + 2], ax[jj * 8 + 3]),
                  pack_bf16(ax[jj * 8 + 4], ax[jj * 8 + 5]), pack_bf16(ax[jj * 8 + 6], ax[jj * 8 + 7]));
      }
      PROF(7);
      {
        const int t = otid();
        const uint32_t q = t >> 6;
        uint32_t d0 = sb + (t & 63) * 16 + R_MRS + q * 1024;
        uint32_t d2 = q == 3 ? d0 - (R_MRS + 3072) + R_POOL + 4096 : d0 + 8192;
        uint32_t d3 = d0 - R_MRS + R_POOL + 5120 + 4096 + q * 4096;
        ma = sb + R_MRS + (t & 7) * 128 + ((((t >> 3) & 3) ^ (t & 7)) << 4);
        pin(d0); pin(d2); pin(d3); pin(ma);
#pragma unroll 1
        for (int it = s >= 0 ? 0 : SPIN_LIMIT - 1; it < SPIN_LIMIT; it++) {
          uint32_t mn[4];
#pragma unroll
          for (int i = 0; i < 4; i++) {
            mn[i] = min(min(v[i].x, v[i].y), min(v[i].z, v[i].w));
            sts128(i < 2 ? d0 + i * 4096 : (i == 2 ? d2 : d3), v[i]);
            if (mn[i] == 0) v[i] = ld_relaxed128(src + i * 256);
          }
          if (__all_sync(~0u, min(min(mn[0], mn[1]), min(mn[2], mn[3])) != 0)) break;
        }
      }
      PROF(11);
      fence_async();
      PROF(9);
      bar_arrive(1, 288);
      bar_sync(3, 256);
    }
  } else {
    asm volatile("setmaxnreg.dec.sync.aligned.u32 56;");
    constexpr int ROLE = 1; (void)ROLE;
    if (tid == 256) {
      mbar_expect(BAR(B_QKV), c == 2 ? 4096 : 2048);
      mbar_expect(BAR(B_KVX), c == 1 ? 0 : 8192);
      mbar_expect(BAR(B_VX), c == 2 ? 0 : 10240);
    }
    if (c == 0 && tid == 352) {
      mbar_wait(BAR(B_POOL), 0);
      for (int j = 0; j < 5; j++) tma_load3d_mc(sb + R_POOL + j * 5120, &maps.x1, 0, 0, NRSC + j, BAR(B_SSFULL), 7);
      tma_load3d_mc(sb + R_K, &maps.x2, 0, 0, 9, BAR(B_XFULL + 3), 7);
    }
    __syncwarp();
    mbar_wait(BAR(B_WO), 0);
#pragma unroll 1
    for (int s = 0; s < NSEG; s++) {
      if (wp == 3) {
        bar_sync(1, 288);
        if (tid < 356) {
          if (rd_rank() != 0) {
            mbar_wait(BAR(B_XDONE), par(s));
            if (s > 0 && rd_rank() == 2) mbar_wait(BAR(B_TFREE), par(s - 1));
            DELAY(2);
            const int t = otid(), c = rd_rank();
            const uint32_t src = sb + R_K + 10240 - c * 10240 + ((t >> 1) & 1) * 5120, r2 = (t & 1) == 0 ? 0u : (uint32_t)(3 - c);
            bulk_s2c(mapa(src, r2), src, 4096, mapa(c == 1 ? BAR(B_KVX) : BAR(B_VX), r2));
          }
        }
        __syncwarp();
      }
      PROF(2);
      PDUMP();
      if (s == 1 && tid == 256 && rd_head() == 0 && rd_rank() == 0) TL(2);
      if (s > 0 && rd_rank() != 0) {
        DELAY(3);
        const int ln = otid() & 31;
        uint4* z = gPart + ((par(s + 1) * 64 + rd_head() * 2 + rd_rank() - 1) * 32 + (ln >> 2)) * 16 + wp * 4 + (ln & 3);
#pragma unroll
        for (int i = 0; i < 4; i++) st_relaxed128(z + i * 128, 0, 0, 0, 0);
      }
      const bool more = s + 1 < NSEG;
      mbar_wait(BAR(B_KVX), par(s));
      if (more) {
        uint32_t vx, va, wad, had, po;
        {
          const int ln = otid() & 31;
          vx = sb + R_V + (wp >> 1) * 5120 + (ln & 15) * 128 + ((((wp & 1) * 4 + (ln >> 4)) ^ (ln & 7)) << 4);
          pin(vx);
          va = sb + R_V + (wp >> 1) * 5120 + 4096 + (ln & 7) * 128 + ((((wp & 1) * 4 + (ln >> 3)) ^ (ln & 7)) << 4);
          wad = sb + R_W4 + (((ln >> 4) & 1) * 8 + (ln & 7)) * 128 + (((wp * 2 + ((ln >> 3) & 1)) ^ (ln & 7)) << 4);
          had = sb + R_Q + (((ln >> 4) & 1) * 8 + (ln & 7)) * 64 + (((wp * 2 + ((ln >> 3) & 1)) ^ ((ln >> 1) & 3)) << 4);
          po = ((par(s) * 64 + 48 + rd_rank() * 4 + wp) * 32 + rd_head()) * 256 + ((ln & 3) * 8 + (ln >> 2)) * 8;
          pin(va); pin(wad); pin(had); pin(po);
        }
        mbar_wait(BAR(B_QKV), par(s));
        PROF(3);
        fence_async();
        float sc[20];
        ZERO(sc, 20);
        WG_FENCE();
#pragma unroll
        for (int j = 0; j < 8; j++) {
          Desc da = mkd(s16, R_Q + 4096 + (j >> 2) * 5120 + (j & 3) * 32, 0, 0, 1);
          Desc db = mkd(s16, R_K + (j >> 2) * 5120 + (j & 3) * 32, 0, 1024, 1);
          wg_ss40<0, 0>(sc, da, db, j > 0);
        }
        WG_COMMIT();
        mbar_wait(BAR(B_VX), par(s));
        WG_WAIT(0);
        PROF(4);
        bar_sync(5, 160);
        uint32_t vf[16], vm[4];
#pragma unroll
        for (int i = 0; i < 4; i++) ldsm4_t(vf + i * 4, (vx ^ ((i & 1) << 5)) + (i >> 1) * 2048);
        ldsm4_t(vm, va);
        float mx = fmaxf(fmaxf(fmaxf(sc[0], sc[1]), fmaxf(sc[4], sc[5])), fmaxf(fmaxf(sc[8], sc[9]), fmaxf(sc[12], sc[13])));
        mx = fmaxf(mx, fmaxf(sc[16], sc[17]));
        mx = fmaxf(mx, __shfl_xor_sync(~0u, mx, 1));
        mx = fmaxf(mx, __shfl_xor_sync(~0u, mx, 2));
        const float mo = -mx * sl2e;
        uint32_t pk[5];
#pragma unroll
        for (int j = 0; j < 5; j++) pk[j] = pack_bf16(ex2(fmaf(sc[4 * j], sl2e, mo)), ex2(fmaf(sc[4 * j + 1], sl2e, mo)));
        PROF(10);
        float oc[20];
        ZERO(oc, 20);
#pragma unroll
        for (int t = 0; t < 2; t++) {
          const uint32_t a[4] = {pk[2 * t], pk[2 * t], pk[2 * t + 1], pk[2 * t + 1]};
          mma16816(oc + 16, a, 0x3F803F80u, 0x3F803F80u);
#pragma unroll
          for (int n = 0; n < 4; n++) mma16816(oc + n * 4, a, vf[t * 8 + n * 2], vf[t * 8 + n * 2 + 1]);
        }
        mma1688(oc + 16, pk[4], pk[4], 0x3F803F80u);
#pragma unroll
        for (int n = 0; n < 4; n++) mma1688(oc + n * 4, pk[4], pk[4], vm[n]);
        const float inv = rcp(oc[16]);
        const uint32_t oa = sb + R_Q + 4096 + (otid() & 31) * 16;
        sts128(oa + (wp >> 1) * 5120 + (wp & 1) * 512,
               make_uint4(pack_bf16(oc[0] * inv, oc[1] * inv), pack_bf16(oc[4] * inv, oc[5] * inv), pack_bf16(oc[8] * inv, oc[9] * inv), pack_bf16(oc[12] * inv, oc[13] * inv)));
        bar_arrive(7, 384);
        const bool second = wp < 2 && rd_rank() != 0;
        uint32_t af[16];
#pragma unroll
        for (int j = 0; j < 4; j++) ldsm4_t(af + j * 4, wad + j * 2048);
        PROF(6);
        bar_sync(6, 128);
        uint32_t ob[2][4];
        lds128(ob[0], oa);
        lds128(ob[1], oa + 512);
        float a0[4], a1[4];
        ZERO(a0, 4); ZERO(a1, 4);
#pragma unroll
        for (int j = 0; j < 8; j++) {
          mma16816((j & 1) ? a1 : a0, af + (j & 3) * 4, ob[(j >> 1) & 1][(j & 1) * 2], ob[(j >> 1) & 1][(j & 1) * 2 + 1]);
          if (j & 1) __syncwarp();
          if (j < 4) ldsm4_t(af + j * 4, wad + (j + 4) * 2048);
          else if (second) ldsm4_t(af + (j & 3) * 4, had + 5120 + (j & 3) * 1024);
          if (j == 1 || j == 3) lds128(ob[j >> 1], oa + 5120 + (j >> 1) * 512);
        }
        st_relaxed64(reinterpret_cast<char*>(gPart) + po, nz(pack_bf16(a0[0] + a1[0], a0[1] + a1[1])), nz(pack_bf16(a0[2] + a1[2], a0[3] + a1[3])));
        if (second) {
          ZERO(a0, 4); ZERO(a1, 4);
#pragma unroll
          for (int j = 0; j < 8; j++) {
            mma16816((j & 1) ? a1 : a0, af + (j & 3) * 4, ob[(j >> 1) & 1][(j & 1) * 2], ob[(j >> 1) & 1][(j & 1) * 2 + 1]);
            if (j < 4) ldsm4_t(af + j * 4, had + j * 1024);
            if (j == 1 || j == 3) lds128(ob[j >> 1], oa + (j >> 1) * 512);
          }
          st_relaxed64(reinterpret_cast<char*>(gPart) + po + (10 - rd_rank() * 2) * 8192, nz(pack_bf16(a0[0] + a1[0], a0[1] + a1[1])), nz(pack_bf16(a0[2] + a1[2], a0[3] + a1[3])));
        }
        if (rd_rank() != 0) bar_arrive(9, 384);
        if (tid == 352) {
          const int rk = rd_rank();
          mbar_expect(BAR(B_QKV), rk == 2 ? 4096 : 2048);
          mbar_expect(BAR(B_KVX), rk == 1 ? 0 : 8192);
          mbar_expect(BAR(B_VX), rk == 2 ? 0 : 10240);
          if (rk == 1) mbar_arrive_remote(mapa(BAR(B_TFREE), 2));
        }
        __syncwarp();
      } else {
        mbar_wait(BAR(B_QKV), par(s));
        mbar_wait(BAR(B_VX), par(s));
      }
      PROF(12);
      if (rd_rank() == 0) {
        fence_async();
        {
          float sc[20];
          ZERO(sc, 20);
          WG_FENCE();
#pragma unroll
          for (int j = 0; j < 8; j++)
            wg_ss40<0, 0>(sc, mkd(s16, R_Q + (j >> 2) * 5120 + (j & 3) * 32, 0, 1024, 1), mkd(s16, R_K + (j >> 2) * 5120 + (j & 3) * 32, 0, 1024, 1), j > 0);
          WG_COMMIT();
          if (more) bar_arrive(9, 384);
          WG_WAIT(0);
          bar_sync(6, 128);
          if (wp < 2) {
            const int ln = otid() & 31;
            const uint32_t pa = sb + R_PX + wp * 1536 + ln * 4;
            float mx[2], sum[2];
#pragma unroll
            for (int hf = 0; hf < 2; hf++) {
              const int lim = wp * 16 + hf * 8 + (ln >> 2) - (ln & 3) * 2;
              mx[hf] = -3.0e38f;
#pragma unroll
              for (int j = 0; j < 10; j++) {
                float& v = sc[(j >> 1) * 4 + hf * 2 + (j & 1)];
                v = (j >= 8 || (j >> 1) * 8 + (j & 1) <= lim) ? v * sl2e : -1.4426950408889634e9f;
                mx[hf] = fmaxf(mx[hf], v);
              }
            }
#pragma unroll
            for (int o = 1; o <= 2; o <<= 1) { mx[0] = fmaxf(mx[0], __shfl_xor_sync(~0u, mx[0], o)); mx[1] = fmaxf(mx[1], __shfl_xor_sync(~0u, mx[1], o)); }
#pragma unroll
            for (int hf = 0; hf < 2; hf++) {
              sum[hf] = 0.f;
#pragma unroll
              for (int j = 0; j < 10; j++) { float& v = sc[(j >> 1) * 4 + hf * 2 + (j & 1)]; v = ex2(v - mx[hf]); sum[hf] += v; }
            }
#pragma unroll
            for (int o = 1; o <= 2; o <<= 1) { sum[0] += __shfl_xor_sync(~0u, sum[0], o); sum[1] += __shfl_xor_sync(~0u, sum[1], o); }
#pragma unroll
            for (int hf = 0; hf < 2; hf++) {
              const float inv = rcp(sum[hf]);
#pragma unroll
              for (int j = 0; j < 5; j++) sts32(pa + hf * 768 + j * 128, pack_bf16(sc[j * 4 + hf * 2] * inv, sc[j * 4 + hf * 2 + 1] * inv));
              sts32(pa + hf * 768 + 640, 0);
            }
            fence_async();
          } else if (tid == 352 && more) {
            tma_load3d_mc(sb + R_K, &maps.x2, 0, (s + 1) * SEG, 9, BAR(B_XFULL + 3), 1);
          }
          __syncwarp();
        }
        bar_sync(6, 128);
        const int ln = otid() & 31, r = ln & 7, blk = ln >> 3;
        const uint32_t oa = sb + R_V + ((blk >> 1) * 8 + r) * 128 + (((wp * 2 + (blk & 1)) ^ r) << 4);
#pragma unroll
        for (int tl = 0; tl < 2; tl++) {
          float ox[16];
          ZERO(ox, 16);
          WG_FENCE();
#pragma unroll
          for (int j = 0; j < 3; j++)
            wg_ss32<1, 0>(ox, mkd(s16, R_V + tl * 5120 + j * 2048, 0, 1024, 1), mkd(s16, R_PX + j * 256, 128, 768, 0), j > 0);
          WG_COMMIT();
          WG_WAIT(0);
          bar_sync(6, 128);
          if (tl == 1 && more && tid == 288) mbar_arrive(BAR(B_TFREE));
#pragma unroll
          for (int jj = 0; jj < 2; jj++) {
            const float* a = ox + jj * 8;
            stsm4_t(oa + tl * 5120 + jj * 2048, pack_bf16(a[0], a[1]), pack_bf16(a[2], a[3]), pack_bf16(a[4], a[5]), pack_bf16(a[6], a[7]));
          }
        }
        fence_async();
        bar_sync(6, 128);
        if (tid == 256) {
          const int hh = rd_head();
          tma_store2d(&maps.ox, sb + R_V, hh * 128, s * SEG);
          tma_store2d(&maps.ox, sb + R_V + 5120, hh * 128 + 64, s * SEG);
          bulk_commit();
          bulk_wait_read0();
          if (more) mbar_arrive_remote(mapa(BAR(B_TFREE), 2));
          bulk_wait0();
          asm volatile("fence.proxy.async;" ::: "memory");
          asm volatile("red.release.gpu.global.add.u32 [%0], 1;" :: "l"(&gSync[SY_OX + (s >> 2)]) : "memory");
        }
        __syncwarp();
        PROF(7);
      } else if (more) {
        const int ln = otid() & 31, cg = rd_head() * 2 + rd_rank() - 1;
        const int n = wp * 2 + ((ln >> 3) & 1);
        const int wi = cg < 48 ? (ln & 3) * 2 + ((ln >> 2) & 1) : (ln & 7);
        uint32_t* dst = reinterpret_cast<uint32_t*>(gMem) + ((cg >> 2) * 256 + n * 32 + ((((cg & 3) * 2 + (wi >> 2)) ^ n) << 2) + (wi & 3) + (ln >> 4) * 16384);
        uint32_t* dpub = dst + ((s + 1) & 3) * 4096;
        const uint4* src = gPart + ((par(s) * 64 + cg) * 32 + (ln >> 2)) * 16 + wp * 4 + (ln & 3);
        uint32_t pubbar = mapa(BAR(B_PUB), ln < 3 ? ln : 0);
        pin(dpub); pin(src); pin(pubbar);
        DELAY(0);
        PROF(11);
        float a[8];
        {
          uint4 v[4];
#pragma unroll
          for (int i = 0; i < 4; i++) v[i] = ld_relaxed128(src + i * 128);
#pragma unroll 1
          for (int it = 0; it < SPIN_LIMIT; it++) {
            uint32_t mn[4];
            ZERO(a, 8);
#pragma unroll
            for (int i = 0; i < 4; i++) {
              mn[i] = min(min(v[i].x, v[i].y), min(v[i].z, v[i].w));
              a[0] += bf_lo(v[i].x); a[1] += bf_lo(v[i].z); a[2] += bf_hi(v[i].x); a[3] += bf_hi(v[i].z);
              a[4] += bf_lo(v[i].y); a[5] += bf_lo(v[i].w); a[6] += bf_hi(v[i].y); a[7] += bf_hi(v[i].w);
              asm volatile("" : "+f"(a[0]), "+f"(a[1]), "+f"(a[2]), "+f"(a[3]), "+f"(a[4]), "+f"(a[5]), "+f"(a[6]), "+f"(a[7]));
              if (mn[i] == 0) v[i] = ld_relaxed128(src + i * 128);
            }
            if (__all_sync(~0u, min(min(mn[0], mn[1]), min(mn[2], mn[3])) != 0)) break;
          }
        }
        __syncwarp();
        PROF(8);
        {
          const bool b2 = (ln & 4) != 0, b3 = (ln & 8) != 0;
          float k[4];
#pragma unroll
          for (int e = 0; e < 4; e++) k[e] = (b2 ? a[4 + e] : a[e]) + __shfl_xor_sync(~0u, b2 ? a[e] : a[4 + e], 4);
          float m0 = (b3 ? k[2] : k[0]) + __shfl_xor_sync(~0u, b3 ? k[0] : k[2], 8);
          float m1 = (b3 ? k[3] : k[1]) + __shfl_xor_sync(~0u, b3 ? k[1] : k[3], 8);
          m0 += __shfl_xor_sync(~0u, m0, 16);
          m1 += __shfl_xor_sync(~0u, m1, 16);
          const uint32_t w = nz(pack_bf16(m0, m1));
#pragma unroll
          for (int r = 0; r < NREP / 2; r++) st_relaxed32(dpub + r * 32768, w);
          if (ln == 3) mbar_arrive(BAR(B_LPUB));
          if (ln < 3) mbar_arrive_remote(pubbar);
#pragma unroll
          for (int r = 0; r < NREP / 2; r++) st_relaxed32(dst + ((s + 3) & 3) * 4096 + r * 32768, 0);
        }
        PROF(9);
      }
    }
    if (tid == 256) bulk_wait0();
    if (tid == 256 && rd_head() == 0 && rd_rank() == 0) TL(3);
  }
  asm volatile("barrier.cluster.arrive.aligned; barrier.cluster.wait.aligned;" ::: "memory");
}

constexpr int G_STAGES = 4;
constexpr uint32_t G_STAGE = 16384 + 32768;
#define TA1 64
#define TA2 64
constexpr int NT_F = 16 * 28, NT_B = 128, NT_A = TA1 + 2 * TA2 + 4 * (128 - TA1 - TA2), NT_ALL = NT_F + NT_B + NT_A;
__device__ __forceinline__ int f_mb(int t) { return (t >= NT_F / 2 ? 8 : 0) + (t & 7); }
__device__ __forceinline__ int f_nb(int t) { return (t >= NT_F / 2 ? t - NT_F / 2 : t) >> 3; }
__device__ __forceinline__ void decode_a(int t, int& tile, int& part, int& lg) {
  if (t < TA1) { tile = t; part = 0; lg = 0; }
  else if (t < TA1 + 2 * TA2) { tile = TA1 + ((t - TA1) >> 1); part = (t - TA1) & 1; lg = 1; }
  else { tile = TA1 + TA2 + ((t - TA1 - 2 * TA2) >> 2); part = (t - TA1 - 2 * TA2) & 3; lg = 2; }
}
constexpr uint32_t G_SMEM = G_STAGES * G_STAGE + 32768 + 256;

struct GemmMaps { CUtensorMap x, wg, wu, hid_st, hid, wd, b_st, ox, wo, out; };

__device__ __forceinline__ void wait_counter(const unsigned* p, unsigned target) {
#pragma unroll 1
  for (int i = 0; i < (1 << 20); i++) {
    unsigned v;
    asm volatile("ld.acquire.gpu.global.u32 %0, [%1];" : "=r"(v) : "l"(p) : "memory");
    if (v >= target) break;
    __nanosleep(40);
  }
}

__global__ void __launch_bounds__(384, 1)
gemm_kernel(const __grid_constant__ GemmMaps maps, const __nv_bfloat16* __restrict__ x, const __nv_bfloat16* __restrict__ gw) {
  extern __shared__ __align__(1024) uint8_t smem[];
  const uint32_t sb = smem_u32(smem);
  const uint32_t sOut = sb + G_STAGES * G_STAGE;
  const uint32_t bars = sOut + 32768;
  const int tid = threadIdx.x, lane = tid & 31;
  const int wid = __shfl_sync(~0u, tid >> 5, 0), wg = wid >> 2, wp = wid & 3;
  volatile int* stask = reinterpret_cast<volatile int*>(smem + G_STAGES * G_STAGE + 32768 + 128);
  if (tid == 0) {
    for (int i = 0; i < G_STAGES; i++) { mbar_init(bars + 8 * i, 1); mbar_init(bars + 32 + 8 * i, 8); }
    for (int i = 0; i < 2; i++) { mbar_init(bars + 64 + 8 * i, 1); mbar_init(bars + 80 + 8 * i, 8); mbar_init(bars + 96 + 8 * i, 1); }
    fence_async();
  }
  __syncthreads();
  if (wg == 2) {
    asm volatile("setmaxnreg.dec.sync.aligned.u32 40;");
    if (wp == 0 && lane == 0) {
      int it = 0;
#pragma unroll 1
      for (int n = 0;; n++) {
        const int task = (int)atomicAdd(&gSync[SY_QUEUE], 1u);
        if (task >= NT_F + NT_B && task < NT_ALL) {
          int tile, part, lg;
          decode_a(task - NT_F - NT_B, tile, part, lg);
          wait_counter(&gSync[SY_GATE], S_LEN / 8);
          wait_counter(&gSync[SY_B + tile], 2);
        }
        gwait(bars + 80 + 8 * (n & 1), ((n >> 1) & 1) ^ 1);
        if (task <= NT_ALL) TL(16 + task);
        if (n == 0) TL(1800 + blockIdx.x);
        stask[n & 1] = task;
        mbar_arrive(bars + 64 + 8 * (n & 1));
        if (task >= NT_ALL) break;
        const CUtensorMap *ta, *tb;
        int mb, nb, nk, k0 = 0;
        if (task < NT_F) { mb = f_mb(task); nb = f_nb(task); nk = DM / 64; ta = &maps.x; tb = &maps.wg; }
        else if (task < NT_F + NT_B) {
          mb = (task - NT_F) >> 3; nb = task & 7; nk = FF / 64; ta = &maps.hid; tb = &maps.wd;
          wait_counter(&gSync[SY_HID + mb], 56);
          asm volatile("fence.proxy.async;" ::: "memory");
        } else {
          int tile, part, lg;
          decode_a(task - NT_F - NT_B, tile, part, lg);
          mb = tile >> 3; nb = tile & 7; nk = (HD / 64) >> lg; k0 = part * nk;
          ta = &maps.ox; tb = &maps.wo;
          wait_counter(&gSync[SY_OX + mb], 4 * NH);
          asm volatile("fence.proxy.async;" ::: "memory");
        }
#pragma unroll 1
        for (int k = 0; k < nk; k++, it++) {
          const int st = it % G_STAGES;
          gwait(bars + 32 + 8 * st, ((it / G_STAGES) & 1) ^ 1);
          const uint32_t d = sb + st * G_STAGE, fb = bars + 8 * st;
          mbar_expect(fb, task < NT_F ? G_STAGE : 32768u);
          tma_load2d(d, ta, (k0 + k) * 64, mb * 128, fb);
          tma_load2d(d + 16384, tb, nb * 128, (k0 + k) * 64, fb);
          tma_load2d(d + 24576, tb, nb * 128 + 64, (k0 + k) * 64, fb);
          if (task < NT_F) {
            tma_load2d(d + 32768, &maps.wu, nb * 128, k * 64, fb);
            tma_load2d(d + 40960, &maps.wu, nb * 128 + 64, k * 64, fb);
          }
        }
      }
    } else if (wp > 0) {
#pragma unroll 1
      while (true) {
        int blk = 0;
        if (lane == 0) blk = (int)atomicAdd(&gSync[SY_GQ], 1u);
        blk = __shfl_sync(~0u, blk, 0);
        if (blk >= S_LEN / 8) break;
        const int row = blk * 8 + (lane >> 2);
        const uint4* xr = reinterpret_cast<const uint4*>(x + (size_t)row * DM) + (lane & 3);
        const uint4* gr = reinterpret_cast<const uint4*>(gw) + (lane & 3);
        float g = 0.f;
#pragma unroll 2
        for (int i = 0; i < 32; i++) {
          const uint4 a = xr[i * 4], b = gr[i * 4];
          g += bf_lo(a.x) * bf_lo(b.x) + bf_hi(a.x) * bf_hi(b.x) + bf_lo(a.y) * bf_lo(b.y) + bf_hi(a.y) * bf_hi(b.y) +
               bf_lo(a.z) * bf_lo(b.z) + bf_hi(a.z) * bf_hi(b.z) + bf_lo(a.w) * bf_lo(b.w) + bf_hi(a.w) * bf_hi(b.w);
        }
        g += __shfl_xor_sync(~0u, g, 1); g += __shfl_xor_sync(~0u, g, 2);
        if ((lane & 3) == 0) gGate[row] = rcp(1.0f + ex2(g * -1.4426950408889634f));
        __threadfence();
        __syncwarp();
        if (lane == 0) asm volatile("red.release.gpu.global.add.u32 [%0], 1;" :: "l"(&gSync[SY_GATE]) : "memory");
      }
      asm volatile("griddepcontrol.wait;" ::: "memory");
      for (int i = blockIdx.x * 96 + (tid - 288); i < 2 * 64 * 32 * 16; i += gridDim.x * 96) gPart[i] = make_uint4(0, 0, 0, 0);
      for (int i = blockIdx.x * 96 + (tid - 288); i < NREP * 4 * 1024; i += gridDim.x * 96) gMem[i] = make_uint4(0, 0, 0, 0);
    }
  } else {
    asm volatile("setmaxnreg.inc.sync.aligned.u32 232;");
    int it = 0, nfin = 0;
    const int r = wg * 64 + wp * 16 + (lane & 7) + ((lane >> 3) & 1) * 8;
#pragma unroll 1
    for (int n = 0;; n++) {
      gwait(bars + 64 + 8 * (n & 1), (n >> 1) & 1);
      const int task = stask[n & 1];
      __syncwarp();
      if (lane == 0) mbar_arrive(bars + 80 + 8 * (n & 1));
      if (task >= NT_ALL) {
        break;
      }
      if (task < NT_F) {
        const int mb = f_mb(task), nb = f_nb(task);
        float acc[128];
        ZERO(acc, 128);
#pragma unroll 1
        for (int k = 0; k < DM / 64; k++, it++) {
          const int st = it % G_STAGES;
          gwait(bars + 8 * st, (it / G_STAGES) & 1);
          const uint32_t d16 = ((sb + st * G_STAGE) & 0x3FFFF) >> 4;
          WG_FENCE();
#pragma unroll
          for (int j = 0; j < 4; j++) wg_ss256<0, 1>(acc, mkd(d16 + wg * 512, j * 32, 0, 1024, 1), mkd(d16, 16384 + j * 2048, 8192, 1024, 1), 1);
          WG_COMMIT();
          if (k > 0) { WG_WAIT(1); if (lane == 0) mbar_arrive(bars + 32 + 8 * ((it - 1) % G_STAGES)); }
        }
        WG_WAIT(0);
        if (lane == 0) mbar_arrive(bars + 32 + 8 * ((it - 1) % G_STAGES));
#pragma unroll
        for (int j = 0; j < 8; j++) {
          uint32_t v[4];
#pragma unroll
          for (int q = 0; q < 4; q++) {
            const float g0 = acc[j * 8 + q * 2], g1 = acc[j * 8 + q * 2 + 1];
            const float u0 = acc[64 + j * 8 + q * 2], u1 = acc[64 + j * 8 + q * 2 + 1];
            v[q] = pack_bf16(g0 * rcp(1.0f + ex2(g0 * -1.4426950408889634f)) * u0, g1 * rcp(1.0f + ex2(g1 * -1.4426950408889634f)) * u1);
          }
          const int g = (j & 3) * 2 + (lane >> 4);
          stsm4(sOut + (j >> 2) * 16384 + r * 128 + ((g ^ (r & 7)) << 4), v[0], v[1], v[2], v[3]);
        }
        fence_async();
        bar_sync(1 + wg, 128);
        if ((tid & 127) == 0) {
          tma_store2d(&maps.hid_st, sOut + wg * 8192, nb * 128, mb * 128 + wg * 64);
          tma_store2d(&maps.hid_st, sOut + 16384 + wg * 8192, nb * 128 + 64, mb * 128 + wg * 64);
          bulk_commit();
          bulk_wait0();
          asm volatile("fence.proxy.async;" ::: "memory");
          asm volatile("red.release.gpu.global.add.u32 [%0], 1;" :: "l"(&gSync[SY_HID + mb]) : "memory");
        }
        bar_sync(1 + wg, 128);
      } else {
        const bool isA = task >= NT_F + NT_B;
        int tile = task - NT_F, part = 0, lg = 0;
        if (isA) decode_a(task - NT_F - NT_B, tile, part, lg);
        const int mb = tile >> 3, nb = tile & 7, nk = isA ? (HD / 64) >> lg : FF / 64, nparts = 1 << lg;
        const bool fin = isA && part + 1 == nparts;
        if (fin && (tid & 127) == 0) {
          asm volatile("fence.proxy.async;" ::: "memory");
          mbar_expect(bars + 96 + 8 * wg, 16384);
          tma_load2d(sOut + wg * 8192, &maps.b_st, nb * 128, mb * 128 + wg * 64, bars + 96 + 8 * wg);
          tma_load2d(sOut + 16384 + wg * 8192, &maps.b_st, nb * 128 + 64, mb * 128 + wg * 64, bars + 96 + 8 * wg);
        }
        __syncwarp();
        float acc[64];
        ZERO(acc, 64);
        if (tid == 0) TL(2048 + task);
#pragma unroll 1
        for (int k = 0; k < nk; k++, it++) {
          const int st = it % G_STAGES;
          gwait(bars + 8 * st, (it / G_STAGES) & 1);
          const uint32_t d16 = ((sb + st * G_STAGE) & 0x3FFFF) >> 4;
          WG_FENCE();
#pragma unroll
          for (int j = 0; j < 4; j++) wg_ss128<0, 1>(acc, mkd(d16 + wg * 512, j * 32, 0, 1024, 1), mkd(d16, 16384 + j * 2048, 8192, 1024, 1), 1);
          WG_COMMIT();
          if (k > 0) { WG_WAIT(1); if (lane == 0) mbar_arrive(bars + 32 + 8 * ((it - 1) % G_STAGES)); }
        }
        if (tid == 0) TL(4096 + task);
        if (part + 1 < nparts) {
          WG_WAIT(0);
          if (lane == 0) mbar_arrive(bars + 32 + 8 * ((it - 1) % G_STAGES));
          float4* tp = gTail + (tile * 3 + part) * 4096 + tid;
#pragma unroll
          for (int j = 0; j < 16; j++) __stcg(tp + j * 256, make_float4(acc[j * 4], acc[j * 4 + 1], acc[j * 4 + 2], acc[j * 4 + 3]));
          __threadfence();
          __syncwarp();
          if (lane == 0) asm volatile("red.release.gpu.global.add.u32 [%0], 1;" :: "l"(&gSync[SY_T + tile]) : "memory");
          if (tid == 0) TL(5120 + task);
          continue;
        }
        float g0 = 0.f, g1 = 0.f;
        if (isA) {
          const int row = mb * 128 + wg * 64 + wp * 16 + (lane >> 2);
          g0 = __ldcg(&gGate[row]); g1 = __ldcg(&gGate[row + 8]);
          gwait(bars + 96 + 8 * wg, nfin & 1);
          nfin++;
        }
        WG_WAIT(0);
        if (lane == 0) mbar_arrive(bars + 32 + 8 * ((it - 1) % G_STAGES));
        if (nparts > 1) {
          if (lane == 0) wait_counter(&gSync[SY_T + tile], 8 * (nparts - 1));
          __syncwarp();
#pragma unroll 1
          for (int pp = 0; pp + 1 < nparts; pp++) {
            const float4* tp = gTail + (tile * 3 + pp) * 4096 + tid;
#pragma unroll
            for (int j = 0; j < 16; j++) {
              const float4 t = __ldcg(tp + j * 256);
              acc[j * 4] += t.x; acc[j * 4 + 1] += t.y; acc[j * 4 + 2] += t.z; acc[j * 4 + 3] += t.w;
            }
          }
        }
#pragma unroll
        for (int j = 0; j < 8; j++) {
          uint32_t v[4], bv[4];
          const uint32_t oa = sOut + (j >> 2) * 16384 + r * 128 + ((((j & 3) * 2 + (lane >> 4)) ^ (r & 7)) << 4);
          if (isA) ldsm4(bv, oa);
#pragma unroll
          for (int q = 0; q < 4; q++) {
            const int i = j * 8 + q * 2;
            if (isA) {
              const float g = (q & 1) ? g1 : g0;
              const uint32_t b = bv[q];
              v[q] = pack_bf16(g * acc[i] + (1.0f - g) * bf_lo(b), g * acc[i + 1] + (1.0f - g) * bf_hi(b));
            } else {
              v[q] = pack_bf16(acc[i], acc[i + 1]);
            }
          }
          stsm4(oa, v[0], v[1], v[2], v[3]);
        }
        fence_async();
        bar_sync(1 + wg, 128);
        if ((tid & 127) == 0) {
          const CUtensorMap* to = isA ? &maps.out : &maps.b_st;
          tma_store2d(to, sOut + wg * 8192, nb * 128, mb * 128 + wg * 64);
          tma_store2d(to, sOut + 16384 + wg * 8192, nb * 128 + 64, mb * 128 + wg * 64);
          bulk_commit();
          bulk_wait0();
          if (!isA) {
            asm volatile("fence.proxy.async;" ::: "memory");
            asm volatile("red.release.gpu.global.add.u32 [%0], 1;" :: "l"(&gSync[SY_B + tile]) : "memory");
          }
        }
        bar_sync(1 + wg, 128);
        if (tid == 0) TL(5120 + task);
      }
    }
  }
}

typedef CUresult (*EncodeFn)(CUtensorMap*, CUtensorMapDataType, cuuint32_t, void*, const cuuint64_t*, const cuuint64_t*,
                             const cuuint32_t*, const cuuint32_t*, CUtensorMapInterleave, CUtensorMapSwizzle,
                             CUtensorMapL2promotion, CUtensorMapFloatOOBfill);

void make_map(EncodeFn fn, CUtensorMap* m, const void* ptr, uint64_t inner, uint64_t outer, uint32_t bi, uint32_t bo,
              CUtensorMapSwizzle swz) {
  cuuint64_t dims[2] = {inner, outer};
  cuuint64_t strides[1] = {inner * 2};
  cuuint32_t box[2] = {bi, bo};
  cuuint32_t es[2] = {1, 1};
  fn(m, CU_TENSOR_MAP_DATA_TYPE_BFLOAT16, 2, const_cast<void*>(ptr), dims, strides, box, es, CU_TENSOR_MAP_INTERLEAVE_NONE, swz,
     CU_TENSOR_MAP_L2_PROMOTION_L2_256B, CU_TENSOR_MAP_FLOAT_OOB_FILL_NONE);
}

}

extern "C" void kernel_launch(void* const* d_in, const int* in_sizes, int n_in, void* d_out, int out_size) {
  (void)in_sizes; (void)n_in; (void)out_size;
  const __nv_bfloat16* x = (const __nv_bfloat16*)d_in[0];
  const __nv_bfloat16* mem0 = (const __nv_bfloat16*)d_in[1];
  const void* Wq = d_in[2]; const void* Wk = d_in[3]; const void* Wv = d_in[4]; const void* Wo = d_in[5];
  const void* Wg = d_in[8]; const void* Wu = d_in[9]; const void* Wd = d_in[10];
  const __nv_bfloat16* gw = (const __nv_bfloat16*)d_in[11];

  void* fnp = nullptr;
  cudaDriverEntryPointQueryResult qr;
  cudaGetDriverEntryPoint("cuTensorMapEncodeTiled", &fnp, cudaEnableDefault, &qr);
  EncodeFn fn = (EncodeFn)fnp;
  void *pOx, *pHid, *pB;
  cudaGetSymbolAddress(&pB, gB);
  cudaGetSymbolAddress(&pOx, gOx);
  cudaGetSymbolAddress(&pHid, gHid);

  const CUtensorMapSwizzle S128 = CU_TENSOR_MAP_SWIZZLE_128B, S64 = CU_TENSOR_MAP_SWIZZLE_64B;
  RecMaps rm;
  make_map(fn, &rm.w[0], Wq, HD, DM, 64, 64, S128);
  make_map(fn, &rm.w[1], Wk, HD, DM, 64, 64, S128);
  make_map(fn, &rm.w[2], Wv, HD, DM, 64, 64, S128);
  make_map(fn, &rm.wo, Wo, DM, HD, 64, 128, S128);
  make_map(fn, &rm.wo_half, Wo, DM, HD, 32, 64, S64);
  {
    cuuint64_t dims[3] = {64, (cuuint64_t)S_LEN, 16};
    cuuint64_t strides[2] = {DM * 2, 128};
    cuuint32_t box[3] = {64, 32, 2};
    cuuint32_t es[3] = {1, 1, 1};
    fn(&rm.x2, CU_TENSOR_MAP_DATA_TYPE_BFLOAT16, 3, (void*)x, dims, strides, box, es, CU_TENSOR_MAP_INTERLEAVE_NONE, S128,
       CU_TENSOR_MAP_L2_PROMOTION_L2_256B, CU_TENSOR_MAP_FLOAT_OOB_FILL_NONE);
    box[2] = 3;
    fn(&rm.x3, CU_TENSOR_MAP_DATA_TYPE_BFLOAT16, 3, (void*)x, dims, strides, box, es, CU_TENSOR_MAP_INTERLEAVE_NONE, S128,
       CU_TENSOR_MAP_L2_PROMOTION_L2_256B, CU_TENSOR_MAP_FLOAT_OOB_FILL_NONE);
    box[2] = 1;
    fn(&rm.x1, CU_TENSOR_MAP_DATA_TYPE_BFLOAT16, 3, (void*)x, dims, strides, box, es, CU_TENSOR_MAP_INTERLEAVE_NONE, S128,
       CU_TENSOR_MAP_L2_PROMOTION_L2_256B, CU_TENSOR_MAP_FLOAT_OOB_FILL_NONE);
  }
  make_map(fn, &rm.ox, pOx, HD, S_LEN, 64, 32, S128);
  GemmMaps gm;
  make_map(fn, &gm.x, x, DM, S_LEN, 64, 128, S128);
  make_map(fn, &gm.wg, Wg, FF, DM, 64, 64, S128);
  make_map(fn, &gm.wu, Wu, FF, DM, 64, 64, S128);
  make_map(fn, &gm.hid_st, pHid, FF, S_LEN, 64, 64, S128);
  make_map(fn, &gm.hid, pHid, FF, S_LEN, 64, 128, S128);
  make_map(fn, &gm.wd, Wd, DM, FF, 64, 64, S128);
  make_map(fn, &gm.b_st, pB, DM, S_LEN, 64, 64, S128);
  make_map(fn, &gm.ox, pOx, HD, S_LEN, 64, 128, S128);
  make_map(fn, &gm.wo, Wo, DM, HD, 64, 64, S128);
  make_map(fn, &gm.out, d_out, DM, S_LEN, 64, 64, S128);

  cudaFuncSetAttribute(rec_kernel, cudaFuncAttributeMaxDynamicSharedMemorySize, REC_SMEM + (REC_PROF ? 768 : 0));
  cudaFuncSetAttribute(gemm_kernel, cudaFuncAttributeMaxDynamicSharedMemorySize, G_SMEM);

  rec_kernel<<<dim3(3, 32), 384, REC_SMEM + (REC_PROF ? 768 : 0), cudaStreamPerThread>>>(rm, mem0, x, (const __nv_bfloat16*)Wo);
  {
    cudaLaunchConfig_t cfg = {};
    cfg.gridDim = dim3(132); cfg.blockDim = dim3(384); cfg.dynamicSmemBytes = G_SMEM; cfg.stream = cudaStreamPerThread;
    cudaLaunchAttribute at[1];
    at[0].id = cudaLaunchAttributeProgrammaticStreamSerialization;
    at[0].val.programmaticStreamSerializationAllowed = 1;
    cfg.attrs = at; cfg.numAttrs = 1;
    cudaLaunchKernelEx(&cfg, gemm_kernel, gm, x, gw);
  }
}
```

```cpp
#include <cuda_runtime.h>
#include <cuda_bf16.h>
#include <cuda.h>
#include <stdint.h>

#define REC_PROF 0

namespace {

constexpr int S_LEN = 2048, DM = 1024, NH = 32, DH = 128, NMEM = 8, SEG = 32, NSEG = 64, FF = 3584;
constexpr int HD = NH * DH;

__device__ __nv_bfloat16 gOx[S_LEN * HD];
__device__ __nv_bfloat16 gHid[S_LEN * FF];
__device__ __nv_bfloat16 gB[S_LEN * DM];
__device__ float gGate[S_LEN];
__device__ float4 gTail[128 * 3 * 16 * 256];
enum { SY_QUEUE = 0, SY_GQ = 8, SY_GATE = 16, SY_HID = 32, SY_OX = 48, SY_B = 64, SY_N = 128 };
__device__ unsigned gTailFlag[128 * 8];
__device__ unsigned gSync[SY_N];
__device__ uint4 gPart[2 * 64 * 32 * 16];
#define NREP 2
__device__ uint4 gMem[NREP * 4 * 1024];

#define TL(i) do {} while (0)
__device__ __forceinline__ uint32_t smem_u32(const void* p) { return (uint32_t)__cvta_generic_to_shared(p); }
__device__ __forceinline__ uint32_t mapa(uint32_t a, uint32_t r) {
  uint32_t o; asm volatile("mapa.shared::cluster.u32 %0, %1, %2;" : "=r"(o) : "r"(a), "r"(r)); return o;
}
__device__ __forceinline__ void mbar_init(uint32_t bar, uint32_t cnt) {
  asm volatile("mbarrier.init.shared::cta.b64 [%0], %1;" :: "r"(bar), "r"(cnt) : "memory");
}
__device__ __forceinline__ void mbar_arrive(uint32_t bar) {
  asm volatile("mbarrier.arrive.shared::cta.b64 _, [%0];" :: "r"(bar) : "memory");
}
__device__ __forceinline__ void mbar_expect(uint32_t bar, uint32_t bytes) {
  asm volatile("mbarrier.arrive.expect_tx.shared::cta.b64 _, [%0], %1;" :: "r"(bar), "r"(bytes) : "memory");
}
__device__ __forceinline__ bool mbar_try(uint32_t bar, uint32_t parity) {
  uint32_t ok;
  asm volatile("{\n.reg .pred p;\nmbarrier.try_wait.parity.shared::cta.b64 p, [%1], %2;\nselp.u32 %0, 1, 0, p;\n}"
               : "=r"(ok) : "r"(bar), "r"(parity) : "memory");
  return ok != 0;
}
constexpr int SPIN_LIMIT = 1 << 15;
__device__ __forceinline__ void mbar_wait(uint32_t bar, uint32_t parity) {
#pragma unroll 1
  for (int i = 0; i < SPIN_LIMIT; i++) if (mbar_try(bar, parity)) break;
}
__device__ __forceinline__ void gwait(uint32_t bar, uint32_t parity) {
#pragma unroll 1
  for (int i = 0; i < (1 << 22); i++) if (mbar_try(bar, parity)) break;
}
__device__ __forceinline__ void fence_async() { asm volatile("fence.proxy.async.shared::cta;" ::: "memory"); }
__device__ __forceinline__ void bar_sync(int id, int n) { asm volatile("bar.sync %0, %1;" :: "r"(id), "r"(n) : "memory"); }
__device__ __forceinline__ void bar_arrive(int id, int n) { asm volatile("bar.arrive %0, %1;" :: "r"(id), "r"(n) : "memory"); }

__device__ __forceinline__ void tma_load2d(uint32_t dst, const CUtensorMap* tm, int c0, int c1, uint32_t bar) {
  asm volatile("cp.async.bulk.tensor.2d.shared::cluster.global.mbarrier::complete_tx::bytes [%0], [%1, {%3, %4}], [%2];"
               :: "r"(dst), "l"(tm), "r"(bar), "r"(c0), "r"(c1) : "memory");
}
__device__ __forceinline__ void tma_load3d_mc(uint32_t dst, const CUtensorMap* tm, int c0, int c1, int c2, uint32_t bar, uint16_t mask) {
  asm volatile("cp.async.bulk.tensor.3d.shared::cluster.global.mbarrier::complete_tx::bytes.multicast::cluster [%0], [%1, {%3, %4, %5}], [%2], %6;"
               :: "r"(dst), "l"(tm), "r"(bar), "r"(c0), "r"(c1), "r"(c2), "h"(mask) : "memory");
}
__device__ __forceinline__ void mbar_arrive_remote(uint32_t bar) {
  asm volatile("mbarrier.arrive.shared::cluster.b64 _, [%0];" :: "r"(bar) : "memory");
}
__device__ __forceinline__ uint32_t clk() { uint32_t t;
  asm volatile("mov.u32 %0, %%clock;" : "=r"(t) :: "memory")
; return t; }
__device__ __forceinline__ uint32_t phase_bad(const uint4& v, uint32_t ph) {
  uint32_t a, b;
  asm("lop3.b32 %0, %1, %2, %3, 0x7E;" : "=r"(a) : "r"(v.x), "r"(v.y), "r"(ph));
  asm("lop3.b32 %0, %1, %2, %3, 0x7E;" : "=r"(b) : "r"(v.z), "r"(v.w), "r"(ph));
  return (a | b) & 1u;
}
__device__ __forceinline__ bool has_zero(const uint4& v) { return min(min(v.x, v.y), min(v.z, v.w)) == 0; }
__device__ __forceinline__ uint32_t par(int s) { uint32_t r; asm volatile("and.b32 %0, %1, 1;" : "=r"(r) : "r"(s)); return r; }
__device__ __forceinline__ bool elect() {
  uint32_t p;
  asm volatile("{\n.reg .pred p;\nelect.sync _|p, 0xffffffff;\nselp.u32 %0, 1, 0, p;\n}" : "=r"(p));
  return p != 0;
}
__device__ __forceinline__ int rd_head() { int v; asm volatile("mov.u32 %0, %%ctaid.y;" : "=r"(v)); return v; }
__device__ __forceinline__ int rd_rank() { int v; asm volatile("mov.u32 %0, %%ctaid.x;" : "=r"(v)); return v; }
template <typename T> __device__ __forceinline__ void pin(T& v) {
  if constexpr (sizeof(T) == 8) asm volatile("" : "+l"(v)); else asm volatile("" : "+r"(v));
}
__device__ __forceinline__ int opaque(int t) { asm volatile("" : "+r"(t)); return t; }
#define otid() opaque(tid)
__device__ __forceinline__ float ex2(float x) { float y; asm("ex2.approx.ftz.f32 %0, %1;" : "=f"(y) : "f"(x)); return y; }
__device__ __forceinline__ float rcp(float x) { float y; asm("rcp.approx.ftz.f32 %0, %1;" : "=f"(y) : "f"(x)); return y; }
__device__ __forceinline__ void tma_prefetch2d(const CUtensorMap* tm, int c0, int c1) {
  asm volatile("cp.async.bulk.prefetch.tensor.2d.L2.global [%0, {%1, %2}];" :: "l"(tm), "r"(c0), "r"(c1) : "memory");
}
__device__ __forceinline__ void tma_store2d(const CUtensorMap* tm, uint32_t src, int c0, int c1) {
  asm volatile("cp.async.bulk.tensor.2d.global.shared::cta.bulk_group [%0, {%2, %3}], [%1];"
               :: "l"(tm), "r"(src), "r"(c0), "r"(c1) : "memory");
}
__device__ __forceinline__ void bulk_commit() { asm volatile("cp.async.bulk.commit_group;" ::: "memory"); }
__device__ __forceinline__ void bulk_wait_read0() { asm volatile("cp.async.bulk.wait_group.read 0;" ::: "memory"); }
__device__ __forceinline__ void bulk_wait0() { asm volatile("cp.async.bulk.wait_group 0;" ::: "memory"); }
__device__ __forceinline__ void bulk_s2c(uint32_t dst, uint32_t src, uint32_t bytes, uint32_t bar) {
  asm volatile("cp.async.bulk.shared::cluster.shared::cta.mbarrier::complete_tx::bytes [%0], [%1], %2, [%3];"
               :: "r"(dst), "r"(src), "r"(bytes), "r"(bar) : "memory");
}
__device__ __forceinline__ void st_async32(uint32_t dst, uint32_t v, uint32_t bar) {
  asm volatile("st.async.shared::cluster.mbarrier::complete_tx::bytes.u32 [%0], %1, [%2];" :: "r"(dst), "r"(v), "r"(bar) : "memory");
}
__device__ __forceinline__ void sts32(uint32_t a, uint32_t v) { asm volatile("st.shared.u32 [%0], %1;" :: "r"(a), "r"(v) : "memory"); }
__device__ __forceinline__ void sts128(uint32_t a, uint4 v) {
  asm volatile("st.shared.v4.u32 [%0], {%1,%2,%3,%4};" :: "r"(a), "r"(v.x), "r"(v.y), "r"(v.z), "r"(v.w) : "memory");
}
__device__ __forceinline__ uint4 ld_relaxed128(const void* p) {
  uint4 v;
  asm volatile("ld.relaxed.gpu.global.v4.u32 {%0,%1,%2,%3}, [%4];" : "=r"(v.x), "=r"(v.y), "=r"(v.z), "=r"(v.w) : "l"(p) : "memory");
  return v;
}
__device__ __forceinline__ void st_relaxed128(void* p, uint32_t a, uint32_t b, uint32_t c, uint32_t d) {
  asm volatile("st.relaxed.gpu.global.v4.u32 [%0], {%1,%2,%3,%4};" :: "l"(p), "r"(a), "r"(b), "r"(c), "r"(d) : "memory");
}
__device__ __forceinline__ void st_relaxed64(void* p, uint32_t a, uint32_t b) {
  asm volatile("st.relaxed.gpu.global.v2.u32 [%0], {%1,%2};" :: "l"(p), "r"(a), "r"(b) : "memory");
}
__device__ __forceinline__ uint32_t nz(uint32_t w) { return w == 0 ? 0x80000000u : w; }
__device__ __forceinline__ float bf_lo(uint32_t w) { return __uint_as_float(w << 16); }
__device__ __forceinline__ float bf_hi(uint32_t w) { return __uint_as_float(w & 0xFFFF0000u); }
__device__ __forceinline__ void st_relaxed32(void* p, uint32_t a) {
  asm volatile("st.relaxed.gpu.global.u32 [%0], %1;" :: "l"(p), "r"(a) : "memory");
}
__device__ __forceinline__ uint32_t pack_bf16(float lo, float hi) {
  uint32_t r; asm("cvt.rn.bf16x2.f32 %0, %1, %2;" : "=r"(r) : "f"(hi), "f"(lo)); return r;
}
__device__ __forceinline__ void ldsm4_t(uint32_t* r, uint32_t addr) {
  asm volatile("ldmatrix.sync.aligned.m8n8.x4.trans.shared.b16 {%0,%1,%2,%3}, [%4];"
               : "=r"(r[0]), "=r"(r[1]), "=r"(r[2]), "=r"(r[3]) : "r"(addr) : "memory");
}
__device__ __forceinline__ void ldsm4(uint32_t* r, uint32_t addr) {
  asm volatile("ldmatrix.sync.aligned.m8n8.x4.shared.b16 {%0,%1,%2,%3}, [%4];"
               : "=r"(r[0]), "=r"(r[1]), "=r"(r[2]), "=r"(r[3]) : "r"(addr) : "memory");
}
__device__ __forceinline__ void mma16816(float* d, const uint32_t* a, uint32_t b0, uint32_t b1) {
  asm volatile("mma.sync.aligned.m16n8k16.row.col.f32.bf16.bf16.f32 {%0,%1,%2,%3}, {%4,%5,%6,%7}, {%8,%9}, {%0,%1,%2,%3};"
               : "+f"(d[0]), "+f"(d[1]), "+f"(d[2]), "+f"(d[3]) : "r"(a[0]), "r"(a[1]), "r"(a[2]), "r"(a[3]), "r"(b0), "r"(b1));
}
__device__ __forceinline__ void mma1688(float* d, uint32_t a0, uint32_t a1, uint32_t b0) {
  asm volatile("mma.sync.aligned.m16n8k8.row.col.f32.bf16.bf16.f32 {%0,%1,%2,%3}, {%4,%5}, {%6}, {%0,%1,%2,%3};"
               : "+f"(d[0]), "+f"(d[1]), "+f"(d[2]), "+f"(d[3]) : "r"(a0), "r"(a1), "r"(b0));
}
__device__ __forceinline__ void lds128(uint32_t* r, uint32_t addr) {
  asm volatile("ld.shared.v4.u32 {%0,%1,%2,%3}, [%4];" : "=r"(r[0]), "=r"(r[1]), "=r"(r[2]), "=r"(r[3]) : "r"(addr) : "memory");
}
__device__ __forceinline__ void stsm4_t(uint32_t addr, uint32_t a, uint32_t b, uint32_t c, uint32_t d) {
  asm volatile("stmatrix.sync.aligned.m8n8.x4.trans.shared.b16 [%0], {%1,%2,%3,%4};" :: "r"(addr), "r"(a), "r"(b), "r"(c), "r"(d) : "memory");
}
__device__ __forceinline__ void stsm4(uint32_t addr, uint32_t a, uint32_t b, uint32_t c, uint32_t d) {
  asm volatile("stmatrix.sync.aligned.m8n8.x4.shared.b16 [%0], {%1,%2,%3,%4};" :: "r"(addr), "r"(a), "r"(b), "r"(c), "r"(d) : "memory");
}
__device__ __forceinline__ uint32_t movm_t(uint32_t a) {
  uint32_t d; asm volatile("movmatrix.sync.aligned.m8n8.trans.b16 %0, %1;" : "=r"(d) : "r"(a)); return d;
}

struct Desc { uint32_t base, off, hi; };
__device__ __forceinline__ Desc mkd(uint32_t base, uint32_t boff, uint32_t lbo, uint32_t sbo, uint32_t swz) {
  return Desc{base, (boff >> 4) + ((lbo >> 4) << 16), (sbo >> 4) | (swz << 30)};
}
#define WG_FENCE() asm volatile("wgmma.fence.sync.aligned;" ::: "memory")
#define WG_COMMIT() asm volatile("wgmma.commit_group.sync.aligned;" ::: "memory")
#define WG_WAIT(n) asm volatile("wgmma.wait_group.sync.aligned " #n ";" ::: "memory")

#define ZERO(a, n) _Pragma("unroll") for (int _i = 0; _i < n; _i++) a[_i] = 0.f
#define F4(d, o) "+f"(d[o]), "+f"(d[o + 1]), "+f"(d[o + 2]), "+f"(d[o + 3])
#define F16(d, o) F4(d, o), F4(d, o + 4), F4(d, o + 8), F4(d, o + 12)
#define F64(d, o) F16(d, o), F16(d, o + 16), F16(d, o + 32), F16(d, o + 48)

template <int TB> __device__ __forceinline__ void wg_rs8(float* d, const uint32_t* a, Desc b, int sc) {
  asm volatile("{\n.reg .pred p;\n.reg .b32 lb;\n.reg .b64 db;\nsetp.ne.b32 p, %11, 0;\nadd.u32 lb, %8, %9;\nmov.b64 db, {lb, %10};\n"
               "wgmma.mma_async.sync.aligned.m64n8k16.f32.bf16.bf16 {%0,%1,%2,%3}, {%4,%5,%6,%7}, db, p, 1, 1, %12;\n}"
               : F4(d, 0) : "r"(a[0]), "r"(a[1]), "r"(a[2]), "r"(a[3]), "r"(b.base), "r"(b.off), "r"(b.hi), "r"(sc), "n"(TB));
}
template <int TA, int TB> __device__ __forceinline__ void wg_ss8(float* d, Desc a, Desc b, int sc) {
  asm volatile("{\n.reg .pred p;\n.reg .b32 la, lb;\n.reg .b64 da, db;\nsetp.ne.b32 p, %10, 0;\n"
               "add.u32 la, %4, %5;\nmov.b64 da, {la, %6};\nadd.u32 lb, %7, %8;\nmov.b64 db, {lb, %9};\n"
               "wgmma.mma_async.sync.aligned.m64n8k16.f32.bf16.bf16 {%0,%1,%2,%3}, da, db, p, 1, 1, %11, %12;\n}"
               : F4(d, 0) : "r"(a.base), "r"(a.off), "r"(a.hi), "r"(b.base), "r"(b.off), "r"(b.hi), "r"(sc), "n"(TA), "n"(TB));
}
template <int TB> __device__ __forceinline__ void wg_rs32(float* d, const uint32_t* a, Desc b, int sc) {
  asm volatile("{\n.reg .pred p;\n.reg .b32 lb;\n.reg .b64 db;\nsetp.ne.b32 p, %23, 0;\nadd.u32 lb, %20, %21;\nmov.b64 db, {lb, %22};\n"
               "wgmma.mma_async.sync.aligned.m64n32k16.f32.bf16.bf16 {%0,%1,%2,%3,%4,%5,%6,%7,%8,%9,%10,%11,%12,%13,%14,%15}, {%16,%17,%18,%19}, db, p, 1, 1, %24;\n}"
               : F16(d, 0) : "r"(a[0]), "r"(a[1]), "r"(a[2]), "r"(a[3]), "r"(b.base), "r"(b.off), "r"(b.hi), "r"(sc), "n"(TB));
}
template <int TA, int TB> __device__ __forceinline__ void wg_ss32(float* d, Desc a, Desc b, int sc) {
  asm volatile("{\n.reg .pred p;\n.reg .b32 la, lb;\n.reg .b64 da, db;\nsetp.ne.b32 p, %22, 0;\n"
               "add.u32 la, %16, %17;\nmov.b64 da, {la, %18};\nadd.u32 lb, %19, %20;\nmov.b64 db, {lb, %21};\n"
               "wgmma.mma_async.sync.aligned.m64n32k16.f32.bf16.bf16 {%0,%1,%2,%3,%4,%5,%6,%7,%8,%9,%10,%11,%12,%13,%14,%15}, da, db, p, 1, 1, %23, %24;\n}"
               : F16(d, 0) : "r"(a.base), "r"(a.off), "r"(a.hi), "r"(b.base), "r"(b.off), "r"(b.hi), "r"(sc), "n"(TA), "n"(TB));
}
template <int TA, int TB> __device__ __forceinline__ void wg_ss40(float* d, Desc a, Desc b, int sc) {
  asm volatile("{\n.reg .pred p;\n.reg .b32 la, lb;\n.reg .b64 da, db;\nsetp.ne.b32 p, %26, 0;\n"
               "add.u32 la, %20, %21;\nmov.b64 da, {la, %22};\nadd.u32 lb, %23, %24;\nmov.b64 db, {lb, %25};\n"
               "wgmma.mma_async.sync.aligned.m64n40k16.f32.bf16.bf16 {%0,%1,%2,%3,%4,%5,%6,%7,%8,%9,%10,%11,%12,%13,%14,%15,%16,%17,%18,%19}, da, db, p, 1, 1, %27, %28;\n}"
               : F16(d, 0), F4(d, 16) : "r"(a.base), "r"(a.off), "r"(a.hi), "r"(b.base), "r"(b.off), "r"(b.hi), "r"(sc), "n"(TA), "n"(TB));
}
template <int TA, int TB> __device__ __forceinline__ void wg_ss128(float* d, Desc a, Desc b, int sc) {
  asm volatile("{\n.reg .pred p;\n.reg .b32 la, lb;\n.reg .b64 da, db;\nsetp.ne.b32 p, %70, 0;\n"
               "add.u32 la, %64, %65;\nmov.b64 da, {la, %66};\nadd.u32 lb, %67, %68;\nmov.b64 db, {lb, %69};\n"
               "wgmma.mma_async.sync.aligned.m64n128k16.f32.bf16.bf16 {%0,%1,%2,%3,%4,%5,%6,%7,%8,%9,%10,%11,%12,%13,%14,%15,%16,%17,%18,%19,%20,%21,%22,%23,%24,%25,%26,%27,%28,%29,%30,%31,%32,%33,%34,%35,%36,%37,%38,%39,%40,%41,%42,%43,%44,%45,%46,%47,%48,%49,%50,%51,%52,%53,%54,%55,%56,%57,%58,%59,%60,%61,%62,%63}, da, db, p, 1, 1, %71, %72;\n}"
               : F64(d, 0) : "r"(a.base), "r"(a.off), "r"(a.hi), "r"(b.base), "r"(b.off), "r"(b.hi), "r"(sc), "n"(TA), "n"(TB));
}
template <int TA, int TB> __device__ __forceinline__ void wg_ss256(float* d, Desc a, Desc b, int sc) {
  asm volatile("{\n.reg .pred p;\n.reg .b32 la, lb;\n.reg .b64 da, db;\nsetp.ne.b32 p, %134, 0;\n"
               "add.u32 la, %128, %129;\nmov.b64 da, {la, %130};\nadd.u32 lb, %131, %132;\nmov.b64 db, {lb, %133};\n"
               "wgmma.mma_async.sync.aligned.m64n256k16.f32.bf16.bf16 {%0,%1,%2,%3,%4,%5,%6,%7,%8,%9,%10,%11,%12,%13,%14,%15,%16,%17,%18,%19,%20,%21,%22,%23,%24,%25,%26,%27,%28,%29,%30,%31,%32,%33,%34,%35,%36,%37,%38,%39,%40,%41,%42,%43,%44,%45,%46,%47,%48,%49,%50,%51,%52,%53,%54,%55,%56,%57,%58,%59,%60,%61,%62,%63,%64,%65,%66,%67,%68,%69,%70,%71,%72,%73,%74,%75,%76,%77,%78,%79,%80,%81,%82,%83,%84,%85,%86,%87,%88,%89,%90,%91,%92,%93,%94,%95,%96,%97,%98,%99,%100,%101,%102,%103,%104,%105,%106,%107,%108,%109,%110,%111,%112,%113,%114,%115,%116,%117,%118,%119,%120,%121,%122,%123,%124,%125,%126,%127}, da, db, p, 1, 1, %135, %136;\n}"
               : F64(d, 0), F64(d, 64) : "r"(a.base), "r"(a.off), "r"(a.hi), "r"(b.base), "r"(b.off), "r"(b.hi), "r"(sc), "n"(TA), "n"(TB));
}

constexpr int NRSC = 11;
#define GCH 9
#define KV_EARLY 0
#define KVB 4096
#define QCH 2
#define NUE 2
__host__ __device__ constexpr int rs_chunk(int i) { return i == 0 ? 0 : i + NUE; }
__host__ __device__ constexpr int u_chunk(int i) { return i < NUE ? i + 1 : i + 7; }
__host__ __device__ constexpr bool is_u(int ch) { return (ch >= 1 && ch <= NUE) || ch >= 7 + NUE; }
__host__ __device__ constexpr int cls_idx(int ch) { return is_u(ch) ? (ch <= NUE ? ch - 1 : ch - 7) : (ch == 0 ? 0 : ch - NUE); }
constexpr uint32_t R_SS = 0;
constexpr uint32_t R_POOL = 81920;
constexpr uint32_t R_MRS = R_POOL + 25600;
constexpr uint32_t R_V = 118784;
constexpr uint32_t R_K = 129024;
constexpr uint32_t R_Q = 139264;
constexpr uint32_t R_WO = R_Q + 10240;
constexpr uint32_t R_W4 = R_WO + 65536;
constexpr uint32_t R_P0 = R_K + 8192;
constexpr uint32_t R_PX = R_Q + 5120;
constexpr uint32_t R_BAR = 231424;
constexpr uint32_t R_INV = R_BAR + 224;
constexpr uint32_t REC_SMEM = 231680;
enum { B_XFULL = 0, B_SSFULL = 4, B_XDONE = 5, B_PRO = 6, B_SDONE = 7, B_POOL = 8, B_QKV = 9, B_KVX = 10, B_TFREE = 11, B_WSS = 12, B_WO = 13, B_W0 = 14, B_XTILE = 17, B_PUB = 18, B_VX = 19, B_LPUB = 20 };
#define SS_ISSUE 0

struct RecMaps { CUtensorMap w[3]; CUtensorMap wo; CUtensorMap wo_half; CUtensorMap x3; CUtensorMap x2; CUtensorMap x1; CUtensorMap ox; int tune[8]; };

#define PROF(i) do {} while (0)
#define PDUMP() do {} while (0)
#define PVAL(i, v) do {} while (0)
#define PSYNC() do {} while (0)
__device__ constexpr int kDelay[8] = {220, 220, 0, 1000, 0, 0, 0, 0};
#define DELAY(i) do { if (kDelay[i] > 0) { unsigned _t0 = clock(); while ((int)(clock() - _t0) < kDelay[i]) {} } } while (0)

__global__ void __cluster_dims__(3, 1, 1) __launch_bounds__(384, 1)
rec_kernel(const __grid_constant__ RecMaps maps, const __nv_bfloat16* __restrict__ mem0, const __nv_bfloat16* __restrict__ xg,
           const __nv_bfloat16* __restrict__ wog) {
  extern __shared__ __align__(1024) uint8_t smem[];
  const uint32_t sb = smem_u32(smem);
  const int tid = opaque(threadIdx.x);
  const int wid = __shfl_sync(~0u, tid >> 5, 0), wg = wid >> 2, wp = wid & 3;
  const uint32_t s16 = (sb & 0x3FFFF) >> 4;
  const int h = blockIdx.y, c = blockIdx.x;
  const uint32_t bars = sb + R_BAR;
  auto BAR = [&](int i) { return bars + 8u * i; };
  const uint32_t sWo = sb + R_WO;

  if (tid == 0 && h == 0 && c == 0) TL(0);
  if (tid == 0) {
    for (int i = 0; i < 5; i++) mbar_init(BAR(B_XFULL + i), 1);
    mbar_init(BAR(B_XDONE), 24); mbar_init(BAR(B_XTILE), 24); mbar_init(BAR(B_PUB), 8); mbar_init(BAR(B_LPUB), 4); mbar_init(BAR(B_VX), c == 2 ? 9 : 1); mbar_init(BAR(B_PRO), 24); mbar_init(BAR(B_SDONE), 2); mbar_init(BAR(B_POOL), 3);
    mbar_init(BAR(B_QKV), c == 2 ? 1 : 9); mbar_init(BAR(B_KVX), 1); mbar_init(BAR(B_TFREE), c == 0 ? 1 : 2);
    mbar_init(BAR(B_WSS), 1); mbar_init(BAR(B_WO), 1);
    for (int i = 0; i < 3; i++) mbar_init(BAR(B_W0 + i), 1);
    asm volatile("fence.mbarrier_init.release.cluster;" ::: "memory");
    fence_async();
    mbar_expect(BAR(B_W0 + 0), 81920); mbar_expect(BAR(B_W0 + 1), 32768); mbar_expect(BAR(B_W0 + 2), 65536);
  }
  if (h == 0 && c == 0 && tid < SY_N) { gSync[tid] = 0; __threadfence(); }
  __syncthreads();
  asm volatile("barrier.cluster.arrive.relaxed.aligned;" ::: "memory");
  asm volatile("griddepcontrol.launch_dependents;" ::: "memory");
  if ((tid & 31) == 0) {
    if (wid < NRSC) {
      const int i = wid;
      const int ch = i < 7 ? rs_chunk(i) : u_chunk(i - 7);
      const uint32_t dst = i < 5 ? sb + R_SS + i * 16384 : (i < 7 ? sb + R_POOL + (i - 5) * 16384 : sWo + (i - 7) * 8192);
      const uint32_t bar = BAR(B_W0 + (i < 5 ? 0 : (i < 7 ? 1 : 2)));
      tma_load2d(dst, &maps.w[c], h * 128, ch * 64, bar);
      tma_load2d(dst + (i < 7 ? 8192 : 32768), &maps.w[c], h * 128 + 64, ch * 64, bar);
    } else if (h * 3 + c < 8) {
      asm volatile("cp.async.bulk.prefetch.L2.global [%0], %1;" :: "l"(reinterpret_cast<const char*>(xg) + (h * 3 + c) * 32768), "r"(32768) : "memory");
    }
  }
  __syncwarp();
  asm volatile("barrier.cluster.wait.aligned;" ::: "memory");

  { constexpr int ROLE = 0; PROF(15); (void)ROLE; }

  const float sl2e = 0.08838834764831845f * 1.4426950408889634f;
  if (wg < 2) {
    asm volatile("setmaxnreg.inc.sync.aligned.u32 224;");
    constexpr int ROLE = 0; (void)ROLE;
    uint32_t wa[28 * 4], wo[16 * 4];
#pragma unroll
    for (int i = 0; i < 64; i++) wo[i] = 0;
    {
      const uint32_t fo = (((tid >> 4) & 1) * 8 + (tid & 7)) * 128 + (((wp * 2 + ((tid >> 3) & 1)) ^ (tid & 7)) << 4);
#pragma unroll
      for (int i = 0; i < 7; i++) {
        if (i % 5 == 0) mbar_wait(BAR(B_W0 + i / 5), 0);
        if (i == 0 && tid == 0 && h == 0 && c == 0) TL(5);
        const uint32_t src = (i < 5 ? sb + R_SS + i * 16384 : sb + R_POOL + (i - 5) * 16384) + wg * 8192 + fo;
#pragma unroll
        for (int j = 0; j < 4; j++) ldsm4_t(&wa[(i * 4 + j) * 4], src + j * 2048);
        if (i == 4) {
          bar_sync(3, 256);
          if (tid == 0) { fence_async(); mbar_expect(BAR(B_WSS), 81920); }
          if ((tid & 31) == 0 && wid >= 1 && wid < 6) {
            fence_async();
            for (int t = 0; t < 2; t++)
              tma_load2d(sb + R_SS + t * 40960 + (wid - 1) * 8192, &maps.w[c], h * 128 + t * 64, (NRSC + wid - 1) * 64, BAR(B_WSS));
          }
          __syncwarp();
        }
      }
      bar_sync(3, 256);
      if (tid == 0) {
        fence_async();
        mbar_arrive_remote(mapa(BAR(B_POOL), 0));
        mbar_expect(BAR(B_WO), c == 0 ? 16384 : 24576);
        tma_load2d(sb + R_W4, &maps.wo, (12 + c) * 64, h * 128, BAR(B_WO));
        if (c != 0) {
          tma_load2d(sb + R_Q, &maps.wo_half, 928 + c * 32, h * 128, BAR(B_WO));
          tma_load2d(sb + R_Q + 5120, &maps.wo_half, 928 + c * 32, h * 128 + 64, BAR(B_WO));
        }
      } else if (tid == 32) {
        for (int t = 0; t < 4; t++) tma_prefetch2d(&maps.wo, ((t >> 1) * 6 + c * 2 + (t & 1)) * 64, h * 128);
      } else if (tid == 64) {
        const uint32_t per = 40960;
        asm volatile("cp.async.bulk.prefetch.L2.global [%0], %1;" :: "l"(reinterpret_cast<const char*>(xg) + 262144 + (h * 3 + c) * per), "r"(per) : "memory");
      }
      __syncwarp();
    }
    mbar_wait(BAR(B_WSS), 0);
    mbar_wait(BAR(B_W0 + 2), 0);
    if (tid == 0 && h == 0 && c == 0) TL(6);
    const uint32_t aSS = s16 + (R_SS >> 4) + wg * 2560;
    const uint32_t aU = s16 + (R_WO >> 4) + wg * 2048;
#define TBASE (R_Q - rd_rank() * 10240)
    PROF(0);
    if (tid == 0 && h == 0 && c == 0) TL(1);
    if (tid == 4) mbar_expect(BAR(B_SSFULL), 20480);
    __syncwarp();
    uint32_t ma = 0;

#pragma unroll 1
    for (int s = -1; s < NSEG; s++) {
      float mr[4];
      ZERO(mr, 4);
      if (s >= 0) {
        float am[12];
        ZERO(am, 12);
        uint32_t bf[4][4];
#pragma unroll
        for (int j = 0; j < 3; j++) ldsm4(bf[j], (ma ^ ((j & 1) << 6)) + rs_chunk(j >> 1) * 1024);
#pragma unroll
        for (int j = 0; j < 14; j++) {
          if (j + 3 < 14) ldsm4(bf[(j + 3) & 3], (ma ^ (((j + 3) & 1) << 6)) + rs_chunk((j + 3) >> 1) * 1024);
          mma16816((j & 1) ? am + 4 : mr, &wa[j * 8], bf[j & 3][0], bf[j & 3][1]);
          mma16816((j & 1) ? am + 8 : am, &wa[j * 8 + 4], bf[j & 3][2], bf[j & 3][3]);
        }
#pragma unroll
        for (int e = 0; e < 4; e++) mr[e] = (mr[e] + am[e]) + (am[4 + e] + am[8 + e]);
        PROF(8);
      }
      PROF(1);
      float a40[20];
      ZERO(a40, 16);
#pragma unroll
      for (int e = 0; e < 4; e++) a40[16 + e] = mr[e];
      float au[4];
      ZERO(au, 4);
      WG_FENCE();
#pragma unroll
      for (int j = 0; j < 16; j++)
        wg_ss8<1, 0>(au, mkd(aU, j * 2048, 0, 1024, 1), mkd(s16, R_MRS + u_chunk(j >> 2) * 1024 + (j & 3) * 32, 0, 1024, 1), 1);
      WG_COMMIT();
      if (s + 1 < NSEG) mbar_wait(BAR(B_SSFULL), (s + 1) & 1);
      WG_FENCE();
#pragma unroll
      for (int j = 0; j < 20; j++)
        wg_ss40<1, 0>(a40, mkd(aSS, j * 2048, 0, 1024, 1), mkd(s16, R_POOL + (j >> 2) * 5120 + (j & 3) * 32, 0, 1024, 1), 1);
      WG_COMMIT();
      uint32_t o0, o1, o2, rb0, rb1, rb2;
      {
        const int ln = otid() & 31, tok = ln >> 2, rk = rd_rank();
        o0 = sb + R_Q - rk * 10240 + wg * 5120 + 4096 + tok * 128 + (((wp * 2) ^ tok) << 4) + (ln & 3) * 4;
        const uint32_t r1 = rk == 2 ? 0 : rk + 1, r2 = rk == 0 ? 2 : rk - 1;
        rb0 = rk == 2 ? BAR(B_VX) : BAR(B_QKV);
        o1 = mapa(o0, r1); o2 = mapa(o0, r2); rb1 = mapa(rb0, r1); rb2 = mapa(rb0, r2);
      }
      WG_WAIT(0);
      float ax[16];
#pragma unroll
      for (int e = 0; e < 16; e++) ax[e] = a40[e];
      if (s >= 0) {
        PROF(2);
        const uint32_t m0 = movm_t(pack_bf16(a40[16] + au[0], a40[17] + au[1]));
        const uint32_t m1 = movm_t(pack_bf16(a40[18] + au[2], a40[19] + au[3]));
        st_async32(o1, m0, rb1);
        st_async32(o2, m0, rb2);
        st_async32(o1 ^ 16, m1, rb1);
        st_async32(o2 ^ 16, m1, rb2);
        sts32(o0, m0);
        sts32(o0 ^ 16, m1);
        __syncwarp();
        if (elect()) mbar_arrive(rb0);
      }
      if (s + 1 < NSEG && elect()) mbar_arrive_remote(mapa(BAR(B_PRO), 0));
      if (s == NSEG - 1) break;
      if (tid < 5 && (tid < 4 || s + 2 < NSEG)) mbar_expect(BAR(B_XFULL + tid), tid < 3 ? 12288 : (tid == 3 ? 8192 : 20480));
      if (c == 0 && tid == 224) {
        mbar_wait(BAR(B_PRO), (s + 1) & 1);
        for (int j = 0; j < 3; j++) tma_load3d_mc(sb + R_POOL + j * 12288, &maps.x3, 0, (s + 1) * SEG, j * 3, BAR(B_XFULL + j), 7);
      }
      __syncwarp();
      if (s <= 0) {
        const int t = otid();
        const uint2* wp0 = reinterpret_cast<const uint2*>(wog + (size_t)(rd_head() * 128 + ((t & 31) >> 2)) * DM + (rd_rank() * 2 + wg) * 64 + wp * 16) + (t & 3);
        if (s < 0) {
#pragma unroll
          for (int i = 0; i < 16; i++) { const uint2 u = __ldg(wp0 + i * 8 * (DM / 4)); wo[2 * i] = u.x; wo[2 * i + 1] = u.y; }
        } else {
#pragma unroll
          for (int i = 0; i < 16; i++) { const uint2 u = __ldg(wp0 + i * 8 * (DM / 4) + 96); wo[32 + 2 * i] = u.x; wo[33 + 2 * i] = u.y; }
#pragma unroll
          for (int i = 0; i < 64; i++) wo[i] = movm_t(wo[i]);
        }
      }
      if (s >= 0) {
        PROF(3);
        PDUMP();
        const int ln = otid() & 31;
        uint32_t pdst = (((s & 1) * 64 + rd_rank() * 8 + wg * 4 + wp) * 32 + rd_head()) * 256 + ((ln & 3) * 8 + (ln >> 2)) * 8;
        uint32_t oa = sb + R_Q + 4096 + ln * 16;
        pin(pdst); pin(oa);
        if (wid == 6) {
          bar_sync(5, 160);
          const int rk = rd_rank();
          if (tid == 192 && rk != 0) tma_load3d_mc(sb + R_K, &maps.x2, 0, (s + 1) * SEG, 9, BAR(B_XFULL + 3), (uint16_t)(1 << rk));
          __syncwarp();
        }
        bar_sync(7, 384);
        uint32_t ob[2][4];
        lds128(ob[0], oa);
        lds128(ob[1], oa + 512);
        float a0[4], a1[4];
        ZERO(a0, 4); ZERO(a1, 4);
#pragma unroll
        for (int i = 0; i < 4; i++) {
          mma16816(a0, &wo[i * 8], ob[i & 1][0], ob[i & 1][1]);
          mma16816(a1, &wo[32 + i * 8], ob[i & 1][0], ob[i & 1][1]);
          mma16816(a0, &wo[i * 8 + 4], ob[i & 1][2], ob[i & 1][3]);
          mma16816(a1, &wo[32 + i * 8 + 4], ob[i & 1][2], ob[i & 1][3]);
          if (i < 2) lds128(ob[i & 1], oa + 5120 + i * 512);
        }
        char* pd = reinterpret_cast<char*>(gPart) + pdst;
        st_relaxed64(pd, nz(pack_bf16(a0[0], a0[1])), nz(pack_bf16(a0[2], a0[3])));
        st_relaxed64(pd + 24 * 8192, nz(pack_bf16(a1[0], a1[1])), nz(pack_bf16(a1[2], a1[3])));
        PROF(4);
        mbar_wait(BAR(B_XFULL), (s + 1) & 1);
        bar_sync(9, 384);
        PROF(5);
        DELAY(4);
      }
      uint4 v[4];
      const uint4* src = gMem + ((rd_head() & (NREP - 1)) * 4 + ((s + 1) & 3)) * 1024 + otid();
#pragma unroll
      for (int ch = 0; ch < NRSC; ch++) {
        if (ch % 3 == 0 && (ch > 0 || s < 0)) mbar_wait(BAR(B_XFULL + ch / 3), (s + 1) & 1);
        if (ch == 0) { PROF(13); } else if (ch == 9) { PROF(14); }
        if (ch == 7 + NUE) {
          if (tid == 224 && s + 2 < NSEG && rd_rank() == 1) {
            mbar_wait(BAR(B_XTILE), (s + 1) & 1);
            DELAY(5);
            for (int j = 0; j < 5; j++) tma_load3d_mc(sb + R_POOL + j * 5120, &maps.x1, 0, (s + 2) * SEG, NRSC + j, BAR(B_SSFULL), 7);
          }
          __syncwarp();
          if (s >= 0 && rd_rank() != 0) mbar_wait(BAR(B_LPUB), s & 1);
        }
        if (ch % 3 == 0 || ch == 7 + NUE || ch == GCH + 1 || ch == 7) WG_FENCE();
#pragma unroll
        for (int j = 0; j < 4; j++)
        {
          const Desc db = mkd(s16, (ch < 9 ? R_POOL + ch * 4096 : R_K + (ch - 9) * 4096) + j * 32, 0, 1024, 1);
#define XSKIP 0
          if (is_u(ch)) { if (XSKIP < 1) wg_ss32<1, 0>(ax, mkd(aU, (cls_idx(ch) * 4 + j) * 2048, 0, 1024, 1), db, 1); }
          else if (XSKIP < 2 || ch == 0) wg_rs32<0>(ax, &wa[(cls_idx(ch) * 4 + j) * 4], db, 1);
        }
        if (ch % 3 == 2 || ch == 10 || ch == 6 + NUE || ch == GCH || ch == 6) WG_COMMIT();
        if (ch == 6) {
          WG_WAIT(1);
          if (elect()) mbar_arrive_remote(mapa(BAR(B_XTILE), 1));
        }
        if (ch == GCH) {
          if (s >= 0) {
            mbar_wait(BAR(B_PUB), s & 1);
            DELAY(1);
            PROF(10);
#pragma unroll
            for (int i = 0; i < 4; i++) v[i] = ld_relaxed128(src + i * 256);
          } else {
            const int t = otid(), n = (t >> 3) & 7;
#pragma unroll
            for (int i = 0; i < 4; i++) v[i] = *reinterpret_cast<const uint4*>(mem0 + n * DM + (i * 4 + (t >> 6)) * 64 + ((t & 7) ^ n) * 8);
          }
        }
      }
      WG_WAIT(0);
      { const int ln = otid() & 31; if (ln < 3) mbar_arrive_remote(mapa(BAR(B_XDONE), ln)); }
      PROF(6);
      if (s >= 0 && rd_rank() == 0) mbar_wait(BAR(B_TFREE), s & 1);
      bar_sync(3, 256);
      {
        const int ln = otid() & 31, r = ln & 7, blk = ln >> 3;
        const uint32_t ta = sb + TBASE + wg * 5120 + ((blk >> 1) * 8 + r) * 128 + (((wp * 2 + (blk & 1)) ^ r) << 4);
#pragma unroll
        for (int jj = 0; jj < 2; jj++)
          stsm4_t(ta + jj * 2048, pack_bf16(ax[jj * 8 + 0], ax[jj * 8 + 1]), pack_bf16(ax[jj * 8 + 2], ax[jj * 8 + 3]),
                  pack_bf16(ax[jj * 8 + 4], ax[jj * 8 + 5]), pack_bf16(ax[jj * 8 + 6], ax[jj * 8 + 7]));
      }
      PROF(7);
      {
        const int t = otid();
        const uint32_t q = t >> 6;
        uint32_t d0 = sb + (t & 63) * 16 + R_MRS + q * 1024;
        uint32_t d2 = q == 3 ? d0 - (R_MRS + 3072) + R_POOL + 4096 : d0 + 8192;
        uint32_t d3 = d0 - R_MRS + R_POOL + 5120 + 4096 + q * 4096;
        ma = sb + R_MRS + (t & 7) * 128 + ((((t >> 3) & 3) ^ (t & 7)) << 4);
        pin(d0); pin(d2); pin(d3); pin(ma);
#pragma unroll 1
        for (int it = s >= 0 ? 0 : SPIN_LIMIT - 1; it < SPIN_LIMIT; it++) {
          uint32_t mn[4];
#pragma unroll
          for (int i = 0; i < 4; i++) {
            mn[i] = min(min(v[i].x, v[i].y), min(v[i].z, v[i].w));
            sts128(i < 2 ? d0 + i * 4096 : (i == 2 ? d2 : d3), v[i]);
            if (mn[i] == 0) v[i] = ld_relaxed128(src + i * 256);
          }
          if (__all_sync(~0u, min(min(mn[0], mn[1]), min(mn[2], mn[3])) != 0)) break;
        }
      }
      PROF(11);
      fence_async();
      PROF(9);
      bar_arrive(1, 288);
      bar_sync(3, 256);
    }
  } else {
    asm volatile("setmaxnreg.dec.sync.aligned.u32 56;");
    constexpr int ROLE = 1; (void)ROLE;
    if (tid == 256) {
      mbar_expect(BAR(B_QKV), c == 2 ? 4096 : 2048);
      mbar_expect(BAR(B_KVX), c == 1 ? 0 : 2 * KVB);
      mbar_expect(BAR(B_VX), c == 2 ? 0 : 2048 + 2 * KVB);
    }
    if (c == 0 && tid == 352) {
      mbar_wait(BAR(B_POOL), 0);
      for (int j = 0; j < 5; j++) tma_load3d_mc(sb + R_POOL + j * 5120, &maps.x1, 0, 0, NRSC + j, BAR(B_SSFULL), 7);
      tma_load3d_mc(sb + R_K, &maps.x2, 0, 0, 9, BAR(B_XFULL + 3), 7);
    }
    __syncwarp();
    mbar_wait(BAR(B_WO), 0);
#pragma unroll 1
    for (int s = 0; s < NSEG; s++) {
      if (wp == 3) {
        bar_sync(1, 288);
        if (tid < 356) {
          if (rd_rank() != 0) {
            mbar_wait(BAR(B_XDONE), par(s));
            if (s > 0 && rd_rank() == 2) mbar_wait(BAR(B_TFREE), par(s - 1));
            DELAY(2);
            const int t = otid(), c = rd_rank();
            const uint32_t src = sb + R_K + 10240 - c * 10240 + ((t >> 1) & 1) * 5120, r2 = (t & 1) == 0 ? 0u : (uint32_t)(3 - c);
            bulk_s2c(mapa(src, r2), src, KVB, mapa(c == 1 ? BAR(B_KVX) : BAR(B_VX), r2));
          }
        }
        __syncwarp();
      }
      PROF(2);
      PDUMP();
      if (s == 1 && tid == 256 && rd_head() == 0 && rd_rank() == 0) TL(2);
      if (s > 0 && rd_rank() != 0) {
        DELAY(3);
        const int ln = otid() & 31;
        uint4* z = gPart + ((par(s + 1) * 64 + rd_head() * 2 + rd_rank() - 1) * 32 + (ln >> 2)) * 16 + wp * 4 + (ln & 3);
#pragma unroll
        for (int i = 0; i < 4; i++) st_relaxed128(z + i * 128, 0, 0, 0, 0);
      }
      const bool more = s + 1 < NSEG;
      mbar_wait(BAR(B_KVX), par(s));
      if (more) {
        uint32_t vx, va, wad, had, po;
        {
          const int ln = otid() & 31;
          vx = sb + R_V + (wp >> 1) * 5120 + (ln & 15) * 128 + ((((wp & 1) * 4 + (ln >> 4)) ^ (ln & 7)) << 4);
          pin(vx);
          va = sb + R_V + (wp >> 1) * 5120 + 4096 + (ln & 7) * 128 + ((((wp & 1) * 4 + (ln >> 3)) ^ (ln & 7)) << 4);
          wad = sb + R_W4 + (((ln >> 4) & 1) * 8 + (ln & 7)) * 128 + (((wp * 2 + ((ln >> 3) & 1)) ^ (ln & 7)) << 4);
          had = sb + R_Q + (((ln >> 4) & 1) * 8 + (ln & 7)) * 64 + (((wp * 2 + ((ln >> 3) & 1)) ^ ((ln >> 1) & 3)) << 4);
          po = ((par(s) * 64 + 48 + rd_rank() * 4 + wp) * 32 + rd_head()) * 256 + ((ln & 3) * 8 + (ln >> 2)) * 8;
          pin(va); pin(wad); pin(had); pin(po);
        }
        mbar_wait(BAR(B_QKV), par(s));
        PROF(3);
        fence_async();
        float sc[20];
        ZERO(sc, 20);
        WG_FENCE();
#pragma unroll
        for (int j = 0; j < 8; j++) {
          Desc da = mkd(s16, R_Q + 4096 + (j >> 2) * 5120 + (j & 3) * 32, 0, 0, 1);
          Desc db = mkd(s16, R_K + (j >> 2) * 5120 + (j & 3) * 32, 0, 1024, 1);
          wg_ss40<0, 0>(sc, da, db, j > 0);
        }
        WG_COMMIT();
        mbar_wait(BAR(B_VX), par(s));
        WG_WAIT(0);
        PROF(4);
        bar_sync(5, 160);
        uint32_t vf[16], vm[4];
#pragma unroll
        for (int i = 0; i < 4; i++) ldsm4_t(vf + i * 4, (vx ^ ((i & 1) << 5)) + (i >> 1) * 2048);
        ldsm4_t(vm, va);
        float mx = fmaxf(fmaxf(fmaxf(sc[0], sc[1]), fmaxf(sc[4], sc[5])), fmaxf(fmaxf(sc[8], sc[9]), fmaxf(sc[12], sc[13])));
        mx = fmaxf(mx, fmaxf(sc[16], sc[17]));
        mx = fmaxf(mx, __shfl_xor_sync(~0u, mx, 1));
        mx = fmaxf(mx, __shfl_xor_sync(~0u, mx, 2));
        const float mo = -mx * sl2e;
        uint32_t pk[5];
#pragma unroll
        for (int j = 0; j < 5; j++) pk[j] = pack_bf16(ex2(fmaf(sc[4 * j], sl2e, mo)), ex2(fmaf(sc[4 * j + 1], sl2e, mo)));
        PROF(10);
        float oc[20];
        ZERO(oc, 20);
#pragma unroll
        for (int t = 0; t < 2; t++) {
          const uint32_t a[4] = {pk[2 * t], pk[2 * t], pk[2 * t + 1], pk[2 * t + 1]};
          mma16816(oc + 16, a, 0x3F803F80u, 0x3F803F80u);
#pragma unroll
          for (int n = 0; n < 4; n++) mma16816(oc + n * 4, a, vf[t * 8 + n * 2], vf[t * 8 + n * 2 + 1]);
        }
        mma1688(oc + 16, pk[4], pk[4], 0x3F803F80u);
#pragma unroll
        for (int n = 0; n < 4; n++) mma1688(oc + n * 4, pk[4], pk[4], vm[n]);
        const float inv = rcp(oc[16]);
        const uint32_t oa = sb + R_Q + 4096 + (otid() & 31) * 16;
        sts128(oa + (wp >> 1) * 5120 + (wp & 1) * 512,
               make_uint4(pack_bf16(oc[0] * inv, oc[1] * inv), pack_bf16(oc[4] * inv, oc[5] * inv), pack_bf16(oc[8] * inv, oc[9] * inv), pack_bf16(oc[12] * inv, oc[13] * inv)));
        bar_arrive(7, 384);
        const bool second = wp < 2 && rd_rank() != 0;
        uint32_t af[16], ob[2][4];
        float a0[4], a1[4];
        ZERO(a0, 4); ZERO(a1, 4);
        if (!second) {
#pragma unroll
          for (int j = 0; j < 4; j++) ldsm4_t(af + j * 4, wad + j * 2048);
          PROF(6);
          bar_sync(6, 128);
          lds128(ob[0], oa);
          lds128(ob[1], oa + 512);
#pragma unroll
          for (int j = 0; j < 8; j++) {
            mma16816((j & 1) ? a1 : a0, af + (j & 3) * 4, ob[(j >> 1) & 1][(j & 1) * 2], ob[(j >> 1) & 1][(j & 1) * 2 + 1]);
            if (j & 1) __syncwarp();
            if (j < 4) ldsm4_t(af + j * 4, wad + (j + 4) * 2048);
            if (j == 1 || j == 3) lds128(ob[j >> 1], oa + 5120 + (j >> 1) * 512);
          }
        } else {
          float a2[4], a3[4];
          ZERO(a2, 4); ZERO(a3, 4);
#pragma unroll
          for (int j = 0; j < 2; j++) { ldsm4_t(af + j * 8, wad + j * 2048); ldsm4_t(af + j * 8 + 4, had + j * 1024); }
          PROF(6);
          bar_sync(6, 128);
          lds128(ob[0], oa);
          lds128(ob[1], oa + 512);
#pragma unroll
          for (int j = 0; j < 8; j++) {
            const uint32_t b0 = ob[(j >> 1) & 1][(j & 1) * 2], b1 = ob[(j >> 1) & 1][(j & 1) * 2 + 1];
            mma16816((j & 1) ? a1 : a0, af + (j & 1) * 8, b0, b1);
            mma16816((j & 1) ? a3 : a2, af + (j & 1) * 8 + 4, b0, b1);
            __syncwarp();
            if (j + 2 < 8) {
              ldsm4_t(af + (j & 1) * 8, wad + (j + 2) * 2048);
              ldsm4_t(af + (j & 1) * 8 + 4, had + ((j + 2) >> 2) * 5120 + ((j + 2) & 3) * 1024);
            }
            if (j == 1 || j == 3) lds128(ob[j >> 1], oa + 5120 + (j >> 1) * 512);
          }
          st_relaxed64(reinterpret_cast<char*>(gPart) + po + (10 - rd_rank() * 2) * 8192, nz(pack_bf16(a2[0] + a3[0], a2[1] + a3[1])), nz(pack_bf16(a2[2] + a3[2], a2[3] + a3[3])));
        }
        st_relaxed64(reinterpret_cast<char*>(gPart) + po, nz(pack_bf16(a0[0] + a1[0], a0[1] + a1[1])), nz(pack_bf16(a0[2] + a1[2], a0[3] + a1[3])));
        if (rd_rank() != 0) bar_arrive(9, 384);
        if (tid == 352) {
          const int rk = rd_rank();
          mbar_expect(BAR(B_QKV), rk == 2 ? 4096 : 2048);
          mbar_expect(BAR(B_KVX), rk == 1 ? 0 : 2 * KVB);
          mbar_expect(BAR(B_VX), rk == 2 ? 0 : 2048 + 2 * KVB);
          if (rk == 1) mbar_arrive_remote(mapa(BAR(B_TFREE), 2));
        }
        __syncwarp();
      } else {
        mbar_wait(BAR(B_QKV), par(s));
        mbar_wait(BAR(B_VX), par(s));
      }
      PROF(12);
      if (rd_rank() == 0) {
        fence_async();
        {
          float sc[20];
          ZERO(sc, 20);
          WG_FENCE();
#pragma unroll
          for (int j = 0; j < 8; j++)
            wg_ss40<0, 0>(sc, mkd(s16, R_Q + (j >> 2) * 5120 + (j & 3) * 32, 0, 1024, 1), mkd(s16, R_K + (j >> 2) * 5120 + (j & 3) * 32, 0, 1024, 1), j > 0);
          WG_COMMIT();
          if (more) bar_arrive(9, 384);
          WG_WAIT(0);
          bar_sync(6, 128);
          if (wp < 2) {
            const int ln = otid() & 31;
            const uint32_t pa = sb + R_PX + wp * 1536 + ln * 4;
            float mx[2], sum[2];
#pragma unroll
            for (int hf = 0; hf < 2; hf++) {
              const int lim = wp * 16 + hf * 8 + (ln >> 2) - (ln & 3) * 2;
              mx[hf] = -3.0e38f;
#pragma unroll
              for (int j = 0; j < 10; j++) {
                float& v = sc[(j >> 1) * 4 + hf * 2 + (j & 1)];
                v = (j >= 8 || (j >> 1) * 8 + (j & 1) <= lim) ? v * sl2e : -1.4426950408889634e9f;
                mx[hf] = fmaxf(mx[hf], v);
              }
            }
#pragma unroll
            for (int o = 1; o <= 2; o <<= 1) { mx[0] = fmaxf(mx[0], __shfl_xor_sync(~0u, mx[0], o)); mx[1] = fmaxf(mx[1], __shfl_xor_sync(~0u, mx[1], o)); }
#pragma unroll
            for (int hf = 0; hf < 2; hf++) {
              sum[hf] = 0.f;
#pragma unroll
              for (int j = 0; j < 10; j++) { float& v = sc[(j >> 1) * 4 + hf * 2 + (j & 1)]; v = ex2(v - mx[hf]); sum[hf] += v; }
            }
#pragma unroll
            for (int o = 1; o <= 2; o <<= 1) { sum[0] += __shfl_xor_sync(~0u, sum[0], o); sum[1] += __shfl_xor_sync(~0u, sum[1], o); }
#pragma unroll
            for (int hf = 0; hf < 2; hf++) {
              const float inv = rcp(sum[hf]);
#pragma unroll
              for (int j = 0; j < 5; j++) sts32(pa + hf * 768 + j * 128, pack_bf16(sc[j * 4 + hf * 2] * inv, sc[j * 4 + hf * 2 + 1] * inv));
              sts32(pa + hf * 768 + 640, 0);
            }
            fence_async();
          } else if (tid == 352 && more) {
            tma_load3d_mc(sb + R_K, &maps.x2, 0, (s + 1) * SEG, 9, BAR(B_XFULL + 3), 1);
          }
          __syncwarp();
        }
        bar_sync(6, 128);
        const int ln = otid() & 31, r = ln & 7, blk = ln >> 3;
        const uint32_t oa = sb + R_V + ((blk >> 1) * 8 + r) * 128 + (((wp * 2 + (blk & 1)) ^ r) << 4);
#pragma unroll
        for (int tl = 0; tl < 2; tl++) {
          float ox[16];
          ZERO(ox, 16);
          WG_FENCE();
#pragma unroll
          for (int j = 0; j < 3; j++)
            wg_ss32<1, 0>(ox, mkd(s16, R_V + tl * 5120 + j * 2048, 0, 1024, 1), mkd(s16, R_PX + j * 256, 128, 768, 0), j > 0);
          WG_COMMIT();
          WG_WAIT(0);
          bar_sync(6, 128);
          if (tl == 1 && more && tid == 288) mbar_arrive(BAR(B_TFREE));
#pragma unroll
          for (int jj = 0; jj < 2; jj++) {
            const float* a = ox + jj * 8;
            stsm4_t(oa + tl * 5120 + jj * 2048, pack_bf16(a[0], a[1]), pack_bf16(a[2], a[3]), pack_bf16(a[4], a[5]), pack_bf16(a[6], a[7]));
          }
        }
        fence_async();
        bar_sync(6, 128);
        if (tid == 256) {
          const int hh = rd_head();
          tma_store2d(&maps.ox, sb + R_V, hh * 128, s * SEG);
          tma_store2d(&maps.ox, sb + R_V + 5120, hh * 128 + 64, s * SEG);
          bulk_commit();
          bulk_wait_read0();
          if (more) mbar_arrive_remote(mapa(BAR(B_TFREE), 2));
          bulk_wait0();
          asm volatile("fence.proxy.async;" ::: "memory");
          asm volatile("red.release.gpu.global.add.u32 [%0], 1;" :: "l"(&gSync[SY_OX + (s >> 2)]) : "memory");
        }
        __syncwarp();
        PROF(7);
      } else if (more) {
        const int ln = otid() & 31, cg = rd_head() * 2 + rd_rank() - 1;
        const int n = wp * 2 + ((ln >> 3) & 1);
        const int wi = cg < 48 ? (ln & 3) * 2 + ((ln >> 2) & 1) : (ln & 7);
        uint32_t* dst = reinterpret_cast<uint32_t*>(gMem) + ((cg >> 2) * 256 + n * 32 + ((((cg & 3) * 2 + (wi >> 2)) ^ n) << 2) + (wi & 3) + (ln >> 4) * 16384);
        uint32_t* dpub = dst + ((s + 1) & 3) * 4096;
        const uint4* src = gPart + ((par(s) * 64 + cg) * 32 + (ln >> 2)) * 16 + wp * 4 + (ln & 3);
        uint32_t pubbar = mapa(BAR(B_PUB), ln < 3 ? ln : 0);
        pin(dpub); pin(src); pin(pubbar);
        DELAY(0);
        PROF(11);
        float a[8];
        {
          uint4 v[4];
#pragma unroll
          for (int i = 0; i < 4; i++) v[i] = ld_relaxed128(src + i * 128);
#pragma unroll 1
          for (int it = 0; it < SPIN_LIMIT; it++) {
            uint32_t mn[4];
            ZERO(a, 8);
#pragma unroll
            for (int i = 0; i < 4; i++) {
              mn[i] = min(min(v[i].x, v[i].y), min(v[i].z, v[i].w));
              a[0] += bf_lo(v[i].x); a[1] += bf_lo(v[i].z); a[2] += bf_hi(v[i].x); a[3] += bf_hi(v[i].z);
              a[4] += bf_lo(v[i].y); a[5] += bf_lo(v[i].w); a[6] += bf_hi(v[i].y); a[7] += bf_hi(v[i].w);
              asm volatile("" : "+f"(a[0]), "+f"(a[1]), "+f"(a[2]), "+f"(a[3]), "+f"(a[4]), "+f"(a[5]), "+f"(a[6]), "+f"(a[7]));
              if (mn[i] == 0) v[i] = ld_relaxed128(src + i * 128);
            }
            if (__all_sync(~0u, min(min(mn[0], mn[1]), min(mn[2], mn[3])) != 0)) break;
          }
        }
        __syncwarp();
        PROF(8);
        {
          const bool b2 = (ln & 4) != 0, b3 = (ln & 8) != 0;
          float k[4];
#pragma unroll
          for (int e = 0; e < 4; e++) k[e] = (b2 ? a[4 + e] : a[e]) + __shfl_xor_sync(~0u, b2 ? a[e] : a[4 + e], 4);
          float m0 = (b3 ? k[2] : k[0]) + __shfl_xor_sync(~0u, b3 ? k[0] : k[2], 8);
          float m1 = (b3 ? k[3] : k[1]) + __shfl_xor_sync(~0u, b3 ? k[1] : k[3], 8);
          m0 += __shfl_xor_sync(~0u, m0, 16);
          m1 += __shfl_xor_sync(~0u, m1, 16);
          const uint32_t w = nz(pack_bf16(m0, m1));
#pragma unroll
          for (int r = 0; r < NREP / 2; r++) st_relaxed32(dpub + r * 32768, w);
          if (ln == 3) mbar_arrive(BAR(B_LPUB));
          if (ln < 3) mbar_arrive_remote(pubbar);
#pragma unroll
          for (int r = 0; r < NREP / 2; r++) st_relaxed32(dst + ((s + 3) & 3) * 4096 + r * 32768, 0);
        }
        PROF(9);
      }
    }
    if (tid == 256) bulk_wait0();
    if (tid == 256 && rd_head() == 0 && rd_rank() == 0) TL(3);
  }
  asm volatile("barrier.cluster.arrive.aligned; barrier.cluster.wait.aligned;" ::: "memory");
}

constexpr int G_STAGES = 4;
constexpr uint32_t G_STAGE = 16384 + 32768;
#define MBW 10
#define MB1 3
#define MB2 1
constexpr int NT_F = 16 * 28, NT_B = 64, NT_W = MBW * 4, T_B = NT_F, T_W = T_B + NT_B, T_N = T_W + NT_W;
constexpr int NT_ALL = T_N + MB1 * 8 + MB2 * 16 + (16 - MBW - MB1 - MB2) * 32;
__device__ __forceinline__ int f_mb(int t) { return (t >= NT_F / 2 ? 8 : 0) + (t & 7); }
__device__ __forceinline__ int f_nb(int t) { return (t >= NT_F / 2 ? t - NT_F / 2 : t) >> 3; }
__device__ __forceinline__ void decode_n(int t, int& tile, int& part, int& lg) {
  if (t < MB1 * 8) { tile = MBW * 8 + t; part = 0; lg = 0; }
  else if (t < MB1 * 8 + MB2 * 16) { t -= MB1 * 8; tile = (MBW + MB1) * 8 + (t >> 1); part = t & 1; lg = 1; }
  else { t -= MB1 * 8 + MB2 * 16; tile = (MBW + MB1 + MB2) * 8 + (t >> 2); part = t & 3; lg = 2; }
}
constexpr uint32_t G_SMEM = G_STAGES * G_STAGE + 32768 + 256;

struct GemmMaps { CUtensorMap st[3];   CUtensorMap x, wg, wu, hid, wd, ox, wo; };

__device__ __forceinline__ void wait_counter(const unsigned* p, unsigned target) {
#pragma unroll 1
  for (int i = 0; i < (1 << 20); i++) {
    unsigned v;
    asm volatile("ld.acquire.gpu.global.u32 %0, [%1];" : "=r"(v) : "l"(p) : "memory");
    if (v >= target) break;
    __nanosleep(40);
  }
}

__global__ void __launch_bounds__(384, 1)
gemm_kernel(const __grid_constant__ GemmMaps maps, const __nv_bfloat16* __restrict__ x, const __nv_bfloat16* __restrict__ gw) {
  extern __shared__ __align__(1024) uint8_t smem[];
  const uint32_t sb = smem_u32(smem);
  const uint32_t sOut = sb + G_STAGES * G_STAGE;
  const uint32_t bars = sOut + 32768;
  const int tid = threadIdx.x, lane = tid & 31;
  const int wid = __shfl_sync(~0u, tid >> 5, 0), wg = wid >> 2, wp = wid & 3;
  volatile int* stask = reinterpret_cast<volatile int*>(smem + G_STAGES * G_STAGE + 32768 + 160);
  volatile int* sdesc = stask + 4;
  if (tid == 0) {
    for (int i = 0; i < G_STAGES; i++) { mbar_init(bars + 8 * i, 1); mbar_init(bars + 32 + 8 * i, 8); }
    for (int i = 0; i < 2; i++) {
      mbar_init(bars + 64 + 8 * i, 1); mbar_init(bars + 80 + 8 * i, 8); mbar_init(bars + 96 + 8 * i, 1);
      mbar_init(bars + 112 + 8 * i, 1); mbar_init(bars + 128 + 8 * i, 1);
    }
    mbar_init(bars + 144, 8);
    fence_async();
  }
  __syncthreads();
  if (wg == 2) {
    asm volatile("setmaxnreg.dec.sync.aligned.u32 40;");
    if (wp == 0) {
      int it = 0, task = 0;
#pragma unroll 1
      for (int n = 0;; n++) {
        if (task >= T_W) gwait(bars + 144, (n - 1) & 1);
        if (lane == 0) task = (int)atomicAdd(&gSync[SY_QUEUE], 1u);
        task = __shfl_sync(~0u, task, 0);
        const CUtensorMap *ta = &maps.ox, *tb = &maps.wo, *tb2 = &maps.wo;
        int mb = 0, c0 = 0, c2 = 0, nk = HD / 64, k0 = 0;
        if (task < T_B) {
          mb = f_mb(task); c0 = c2 = f_nb(task) * 128; nk = DM / 64; ta = &maps.x; tb = &maps.wg; tb2 = &maps.wu;
        } else if (task < T_W) {
          mb = (task - T_B) >> 2; c0 = (task & 3) * 256; c2 = c0 + 128; nk = FF / 64; ta = &maps.hid; tb = tb2 = &maps.wd;
          if (lane == 0) wait_counter(&gSync[SY_HID + mb], 56);
        } else if (task < NT_ALL) {
          if (task < T_N) { mb = (task - T_W) >> 2; c0 = (task & 3) * 256; c2 = c0 + 128; }
          else {
            int tile, part, lg;
            decode_n(task - T_N, tile, part, lg);
            mb = tile >> 3; c0 = (tile & 7) * 128; nk >>= lg; k0 = part * nk;
          }
          if (lane < 3) wait_counter(&gSync[lane == 0 ? SY_OX + mb : (lane == 1 ? SY_GATE : SY_B + mb * 4 + (c0 >> 8))], lane == 0 ? 4 * NH : (lane == 1 ? S_LEN / 8 : 4));
        }
        __syncwarp();
        if (lane == 0) {
          gwait(bars + 80 + 8 * (n & 1), ((n >> 1) & 1) ^ 1);
          if (task <= NT_ALL) TL(16 + task);
          if (n == 0) TL(1800 + blockIdx.x);
          stask[n & 1] = task;
          mbar_arrive(bars + 64 + 8 * (n & 1));
          if (task < NT_ALL) {
            asm volatile("fence.proxy.async;" ::: "memory");
#pragma unroll 1
            for (int k = k0; k < k0 + nk; k++, it++) {
              const int st = it % G_STAGES;
              gwait(bars + 32 + 8 * st, ((it / G_STAGES) & 1) ^ 1);
              const uint32_t d = sb + st * G_STAGE, fb = bars + 8 * st;
              mbar_expect(fb, task < T_N ? G_STAGE : 32768u);
              tma_load2d(d, ta, k * 64, mb * 128, fb);
              tma_load2d(d + 16384, tb, c0, k * 64, fb);
              tma_load2d(d + 24576, tb, c0 + 64, k * 64, fb);
              if (task < T_N) {
                tma_load2d(d + 32768, tb2, c2, k * 64, fb);
                tma_load2d(d + 40960, tb2, c2 + 64, k * 64, fb);
              }
            }
          }
        }
        __syncwarp();
        if (task >= NT_ALL) break;
      }
    } else {
#pragma unroll 1
      while (true) {
        int blk = 0;
        if (lane == 0) blk = (int)atomicAdd(&gSync[SY_GQ], 1u);
        blk = __shfl_sync(~0u, blk, 0);
        if (blk >= S_LEN / 8) break;
        const int row = blk * 8 + (lane >> 2);
        const uint4* xr = reinterpret_cast<const uint4*>(x + (size_t)row * DM) + (lane & 3);
        const uint4* gr = reinterpret_cast<const uint4*>(gw) + (lane & 3);
        float g = 0.f;
#pragma unroll 2
        for (int i = 0; i < 32; i++) {
          const uint4 a = xr[i * 4], b = gr[i * 4];
          g += bf_lo(a.x) * bf_lo(b.x) + bf_hi(a.x) * bf_hi(b.x) + bf_lo(a.y) * bf_lo(b.y) + bf_hi(a.y) * bf_hi(b.y) +
               bf_lo(a.z) * bf_lo(b.z) + bf_hi(a.z) * bf_hi(b.z) + bf_lo(a.w) * bf_lo(b.w) + bf_hi(a.w) * bf_hi(b.w);
        }
        g += __shfl_xor_sync(~0u, g, 1); g += __shfl_xor_sync(~0u, g, 2);
        if ((lane & 3) == 0) gGate[row] = rcp(1.0f + ex2(g * -1.4426950408889634f));
        __threadfence();
        __syncwarp();
        if (lane == 0) asm volatile("red.release.gpu.global.add.u32 [%0], 1;" :: "l"(&gSync[SY_GATE]) : "memory");
      }
      if (wp < 3) {
        if (lane == 0) {
          const int w = wp - 1;
#pragma unroll 1
          for (int n = 0;; n++) {
            gwait(bars + 112 + 8 * w, n & 1);
            const int id = sdesc[w * 4], c0 = sdesc[w * 4 + 1], c1 = sdesc[w * 4 + 2], flag = sdesc[w * 4 + 3];
            if (id < 0) break;
            tma_store2d(&maps.st[id], sOut + w * 8192, c0, c1);
            tma_store2d(&maps.st[id], sOut + 16384 + w * 8192, c0 + 64, c1);
            bulk_commit();
            bulk_wait_read0();
            mbar_arrive(bars + 128 + 8 * w);
            bulk_wait0();
            if (flag >= 0) {
              asm volatile("fence.proxy.async;" ::: "memory");
              asm volatile("red.release.gpu.global.add.u32 [%0], 1;" :: "l"(&gSync[flag]) : "memory");
            }
          }
        }
      } else {
        asm volatile("griddepcontrol.wait;" ::: "memory");
        for (int i = blockIdx.x * 32 + lane; i < 2 * 64 * 32 * 16; i += gridDim.x * 32) gPart[i] = make_uint4(0, 0, 0, 0);
        for (int i = blockIdx.x * 32 + lane; i < NREP * 4 * 1024; i += gridDim.x * 32) gMem[i] = make_uint4(0, 0, 0, 0);
      }
    }
  } else {
    asm volatile("setmaxnreg.inc.sync.aligned.u32 232;");
    int it = 0, nb_ld = 0, nst = 0;
    const int r = wg * 64 + wp * 16 + (lane & 7) + ((lane >> 3) & 1) * 8;
    const uint32_t oa0 = sOut + r * 128, osw = (lane >> 4) ^ (r & 7);
    auto stage_acquire = [&]() { gwait(bars + 128 + 8 * wg, (nst & 1) ^ 1); };
    auto stage_emit = [&](int id, int c0, int c1, int flag) {
      fence_async();
      bar_sync(1 + wg, 128);
      if ((tid & 127) == 0) {
        sdesc[wg * 4] = id; sdesc[wg * 4 + 1] = c0; sdesc[wg * 4 + 2] = c1; sdesc[wg * 4 + 3] = flag;
        mbar_arrive(bars + 112 + 8 * wg);
      }
      nst++;
    };
    auto load_b = [&](int c0, int c1) {
      if ((tid & 127) == 0) {
        asm volatile("fence.proxy.async;" ::: "memory");
        mbar_expect(bars + 96 + 8 * wg, 16384);
        tma_load2d(sOut + wg * 8192, &maps.st[1], c0, c1, bars + 96 + 8 * wg);
        tma_load2d(sOut + 16384 + wg * 8192, &maps.st[1], c0 + 64, c1, bars + 96 + 8 * wg);
      }
      __syncwarp();
    };
    auto write_tile = [&](const float* a, bool mix, float g0, float g1) {
      if (mix) { gwait(bars + 96 + 8 * wg, nb_ld & 1); nb_ld++; }
#pragma unroll
      for (int j = 0; j < 8; j++) {
        uint32_t v[4], bv[4];
        const uint32_t oa = oa0 + (j >> 2) * 16384 + ((osw ^ ((j & 3) * 2)) << 4);
        if (mix) ldsm4(bv, oa);
#pragma unroll
        for (int q = 0; q < 4; q++) {
          const int i = j * 8 + q * 2;
          const float g = (q & 1) ? g1 : g0;
          v[q] = mix ? pack_bf16(g * a[i] + (1.0f - g) * bf_lo(bv[q]), g * a[i + 1] + (1.0f - g) * bf_hi(bv[q])) : pack_bf16(a[i], a[i + 1]);
        }
        stsm4(oa, v[0], v[1], v[2], v[3]);
      }
    };
#pragma unroll 1
    for (int n = 0;; n++) {
      gwait(bars + 64 + 8 * (n & 1), (n >> 1) & 1);
      const int task = stask[n & 1];
      __syncwarp();
      if (lane == 0) mbar_arrive(bars + 80 + 8 * (n & 1));
      if (task >= NT_ALL) {
        stage_acquire();
        stage_emit(-1, 0, 0, -1);
        break;
      }
      if (tid == 0) TL(2048 + task);
      if (task < T_N) {
        const bool isF = task < T_B, isA = task >= T_W;
        const int mb = isF ? f_mb(task) : (task - (isA ? T_W : T_B)) >> 2;
        const int c0 = isF ? f_nb(task) * 128 : (task & 3) * 256, c1 = mb * 128 + wg * 64;
        const int nk = isF ? DM / 64 : (isA ? HD / 64 : FF / 64);
        if (isA) { stage_acquire(); load_b(c0, c1); }
        float acc[128];
        ZERO(acc, 128);
#pragma unroll 1
        for (int k = 0; k < nk; k++, it++) {
          const int st = it % G_STAGES;
          gwait(bars + 8 * st, (it / G_STAGES) & 1);
          const uint32_t d16 = ((sb + st * G_STAGE) & 0x3FFFF) >> 4;
          WG_FENCE();
#pragma unroll
          for (int j = 0; j < 4; j++) wg_ss256<0, 1>(acc, mkd(d16 + wg * 512, j * 32, 0, 1024, 1), mkd(d16, 16384 + j * 2048, 8192, 1024, 1), 1);
          WG_COMMIT();
          if (k > 0) { WG_WAIT(1); if (lane == 0) mbar_arrive(bars + 32 + 8 * ((it - 1) % G_STAGES)); }
        }
        float g0 = 0.f, g1 = 0.f;
        if (isA) { g0 = __ldcg(&gGate[c1 + wp * 16 + (lane >> 2)]); g1 = __ldcg(&gGate[c1 + wp * 16 + (lane >> 2) + 8]); }
        else stage_acquire();
        WG_WAIT(0);
        if (lane == 0) mbar_arrive(bars + 32 + 8 * ((it - 1) % G_STAGES));
        if (isF) {
#pragma unroll
          for (int i = 0; i < 64; i++) acc[i] = acc[i] * rcp(1.0f + ex2(acc[i] * -1.4426950408889634f)) * acc[64 + i];
          write_tile(acc, false, 0.f, 0.f);
          stage_emit(0, c0, c1, SY_HID + mb);
        } else {
          const int flag = isA ? -1 : SY_B + (task - T_B);
          write_tile(acc, isA, g0, g1);
          stage_emit(isA ? 2 : 1, c0, c1, flag);
          stage_acquire();
          if (isA) load_b(c0 + 128, c1);
          write_tile(acc + 64, isA, g0, g1);
          stage_emit(isA ? 2 : 1, c0 + 128, c1, flag);
        }
      } else {
        int tile, part, lg;
        decode_n(task - T_N, tile, part, lg);
        const int c0 = (tile & 7) * 128, c1 = (tile >> 3) * 128 + wg * 64, nk = (HD / 64) >> lg, nparts = 1 << lg;
        if (part + 1 == nparts) { stage_acquire(); load_b(c0, c1); }
        float acc[64];
        ZERO(acc, 64);
#pragma unroll 1
        for (int k = 0; k < nk; k++, it++) {
          const int st = it % G_STAGES;
          gwait(bars + 8 * st, (it / G_STAGES) & 1);
          const uint32_t d16 = ((sb + st * G_STAGE) & 0x3FFFF) >> 4;
          WG_FENCE();
#pragma unroll
          for (int j = 0; j < 4; j++) wg_ss128<0, 1>(acc, mkd(d16 + wg * 512, j * 32, 0, 1024, 1), mkd(d16, 16384 + j * 2048, 8192, 1024, 1), 1);
          WG_COMMIT();
          if (k > 0) { WG_WAIT(1); if (lane == 0) mbar_arrive(bars + 32 + 8 * ((it - 1) % G_STAGES)); }
        }
        const float g0 = __ldcg(&gGate[c1 + wp * 16 + (lane >> 2)]), g1 = __ldcg(&gGate[c1 + wp * 16 + (lane >> 2) + 8]);
        WG_WAIT(0);
        if (lane == 0) mbar_arrive(bars + 32 + 8 * ((it - 1) % G_STAGES));
        if (tid == 0) TL(4096 + task);
        if (part + 1 < nparts) {
          float4* tp = gTail + (tile * 3 + part) * 4096 + tid;
#pragma unroll
          for (int j = 0; j < 16; j++) __stcg(tp + j * 256, make_float4(acc[j * 4], acc[j * 4 + 1], acc[j * 4 + 2], acc[j * 4 + 3]));
          __syncwarp();
          if (lane == 0) { __threadfence(); asm volatile("red.relaxed.gpu.global.add.u32 [%0], 1;" :: "l"(&gTailFlag[tile * 8 + wid]) : "memory"); }
        } else {
          if (nparts > 1) {
            if (lane == 0) { wait_counter(&gTailFlag[tile * 8 + wid], nparts - 1); gTailFlag[tile * 8 + wid] = 0; }
            __syncwarp();
            const float4* tp = gTail + tile * 3 * 4096 + tid;
            if (nparts == 2) {
#pragma unroll
              for (int j = 0; j < 16; j++) {
                const float4 t = __ldcg(tp + j * 256);
                acc[j * 4] += t.x; acc[j * 4 + 1] += t.y; acc[j * 4 + 2] += t.z; acc[j * 4 + 3] += t.w;
              }
            } else {
#pragma unroll
              for (int j = 0; j < 16; j++) {
                const float4 t = __ldcg(tp + j * 256), u = __ldcg(tp + 4096 + j * 256), w = __ldcg(tp + 8192 + j * 256);
                acc[j * 4] += t.x + u.x + w.x; acc[j * 4 + 1] += t.y + u.y + w.y; acc[j * 4 + 2] += t.z + u.z + w.z; acc[j * 4 + 3] += t.w + u.w + w.w;
              }
            }
          }
          write_tile(acc, true, g0, g1);
          stage_emit(2, c0, c1, -1);
        }
      }
      if (lane == 0) mbar_arrive(bars + 144);
      if (tid == 0) TL(5120 + task);
    }
  }
}

typedef CUresult (*EncodeFn)(CUtensorMap*, CUtensorMapDataType, cuuint32_t, void*, const cuuint64_t*, const cuuint64_t*,
                             const cuuint32_t*, const cuuint32_t*, CUtensorMapInterleave, CUtensorMapSwizzle,
                             CUtensorMapL2promotion, CUtensorMapFloatOOBfill);

void make_map(EncodeFn fn, CUtensorMap* m, const void* ptr, uint64_t inner, uint64_t outer, uint32_t bi, uint32_t bo,
              CUtensorMapSwizzle swz) {
  cuuint64_t dims[2] = {inner, outer};
  cuuint64_t strides[1] = {inner * 2};
  cuuint32_t box[2] = {bi, bo};
  cuuint32_t es[2] = {1, 1};
  fn(m, CU_TENSOR_MAP_DATA_TYPE_BFLOAT16, 2, const_cast<void*>(ptr), dims, strides, box, es, CU_TENSOR_MAP_INTERLEAVE_NONE, swz,
     CU_TENSOR_MAP_L2_PROMOTION_L2_256B, CU_TENSOR_MAP_FLOAT_OOB_FILL_NONE);
}

}

extern "C" void kernel_launch(void* const* d_in, const int* in_sizes, int n_in, void* d_out, int out_size) {
  (void)in_sizes; (void)n_in; (void)out_size;
  const __nv_bfloat16* x = (const __nv_bfloat16*)d_in[0];
  const __nv_bfloat16* mem0 = (const __nv_bfloat16*)d_in[1];
  const void* Wq = d_in[2]; const void* Wk = d_in[3]; const void* Wv = d_in[4]; const void* Wo = d_in[5];
  const void* Wg = d_in[8]; const void* Wu = d_in[9]; const void* Wd = d_in[10];
  const __nv_bfloat16* gw = (const __nv_bfloat16*)d_in[11];

  void* fnp = nullptr;
  cudaDriverEntryPointQueryResult qr;
  cudaGetDriverEntryPoint("cuTensorMapEncodeTiled", &fnp, cudaEnableDefault, &qr);
  EncodeFn fn = (EncodeFn)fnp;
  void *pOx, *pHid, *pB;
  cudaGetSymbolAddress(&pB, gB);
  cudaGetSymbolAddress(&pOx, gOx);
  cudaGetSymbolAddress(&pHid, gHid);

  const CUtensorMapSwizzle S128 = CU_TENSOR_MAP_SWIZZLE_128B, S64 = CU_TENSOR_MAP_SWIZZLE_64B;
  RecMaps rm;
  make_map(fn, &rm.w[0], Wq, HD, DM, 64, 64, S128);
  make_map(fn, &rm.w[1], Wk, HD, DM, 64, 64, S128);
  make_map(fn, &rm.w[2], Wv, HD, DM, 64, 64, S128);
  make_map(fn, &rm.wo, Wo, DM, HD, 64, 128, S128);
  make_map(fn, &rm.wo_half, Wo, DM, HD, 32, 64, S64);
  {
    cuuint64_t dims[3] = {64, (cuuint64_t)S_LEN, 16};
    cuuint64_t strides[2] = {DM * 2, 128};
    cuuint32_t box[3] = {64, 32, 2};
    cuuint32_t es[3] = {1, 1, 1};
    fn(&rm.x2, CU_TENSOR_MAP_DATA_TYPE_BFLOAT16, 3, (void*)x, dims, strides, box, es, CU_TENSOR_MAP_INTERLEAVE_NONE, S128,
       CU_TENSOR_MAP_L2_PROMOTION_L2_256B, CU_TENSOR_MAP_FLOAT_OOB_FILL_NONE);
    box[2] = 3;
    fn(&rm.x3, CU_TENSOR_MAP_DATA_TYPE_BFLOAT16, 3, (void*)x, dims, strides, box, es, CU_TENSOR_MAP_INTERLEAVE_NONE, S128,
       CU_TENSOR_MAP_L2_PROMOTION_L2_256B, CU_TENSOR_MAP_FLOAT_OOB_FILL_NONE);
    box[2] = 1;
    fn(&rm.x1, CU_TENSOR_MAP_DATA_TYPE_BFLOAT16, 3, (void*)x, dims, strides, box, es, CU_TENSOR_MAP_INTERLEAVE_NONE, S128,
       CU_TENSOR_MAP_L2_PROMOTION_L2_256B, CU_TENSOR_MAP_FLOAT_OOB_FILL_NONE);
  }
  make_map(fn, &rm.ox, pOx, HD, S_LEN, 64, 32, S128);
  GemmMaps gm;
  make_map(fn, &gm.x, x, DM, S_LEN, 64, 128, S128);
  make_map(fn, &gm.wg, Wg, FF, DM, 64, 64, S128);
  make_map(fn, &gm.wu, Wu, FF, DM, 64, 64, S128);
  make_map(fn, &gm.st[0], pHid, FF, S_LEN, 64, 64, S128);
  make_map(fn, &gm.hid, pHid, FF, S_LEN, 64, 128, S128);
  make_map(fn, &gm.wd, Wd, DM, FF, 64, 64, S128);
  make_map(fn, &gm.st[1], pB, DM, S_LEN, 64, 64, S128);
  make_map(fn, &gm.ox, pOx, HD, S_LEN, 64, 128, S128);
  make_map(fn, &gm.wo, Wo, DM, HD, 64, 64, S128);
  make_map(fn, &gm.st[2], d_out, DM, S_LEN, 64, 64, S128);

  cudaFuncSetAttribute(rec_kernel, cudaFuncAttributeMaxDynamicSharedMemorySize, REC_SMEM + (REC_PROF ? 768 : 0));
  cudaFuncSetAttribute(gemm_kernel, cudaFuncAttributeMaxDynamicSharedMemorySize, G_SMEM);

  rec_kernel<<<dim3(3, 32), 384, REC_SMEM + (REC_PROF ? 768 : 0), cudaStreamPerThread>>>(rm, mem0, x, (const __nv_bfloat16*)Wo);
  {
    cudaLaunchConfig_t cfg = {};
    cfg.gridDim = dim3(132); cfg.blockDim = dim3(384); cfg.dynamicSmemBytes = G_SMEM; cfg.stream = cudaStreamPerThread;
    cudaLaunchAttribute at[1];
    at[0].id = cudaLaunchAttributeProgrammaticStreamSerialization;
    at[0].val.programmaticStreamSerializationAllowed = 1;
    cfg.attrs = at; cfg.numAttrs = 1;
    cudaLaunchKernelEx(&cfg, gemm_kernel, gm, x, gw);
  }
}
```

```cpp
#include <cuda_runtime.h>
#include <cuda_bf16.h>
#include <cuda.h>
#include <stdint.h>

#define REC_PROF 0

namespace {

constexpr int S_LEN = 2048, DM = 1024, NH = 32, DH = 128, NMEM = 8, SEG = 32, NSEG = 64, FF = 3584;
constexpr int HD = NH * DH;

__device__ __nv_bfloat16 gOx[S_LEN * HD];
__device__ __nv_bfloat16 gHid[S_LEN * FF];
__device__ __nv_bfloat16 gB[S_LEN * DM];
__device__ float gGate[S_LEN];
__device__ float4 gTail[128 * 3 * 16 * 256];
enum { SY_QUEUE = 0, SY_GQ = 8, SY_GATE = 16, SY_HID = 32, SY_OX = 48, SY_B = 64, SY_N = 128 };
__device__ unsigned gTailFlag[128 * 8];
__device__ unsigned gSync[SY_N];
__device__ uint4 gPart[2 * 64 * 32 * 16];
#define NREP 2
__device__ uint4 gMem[NREP * 4 * 1024];

#define TL(i) do {} while (0)
__device__ __forceinline__ uint32_t smem_u32(const void* p) { return (uint32_t)__cvta_generic_to_shared(p); }
__device__ __forceinline__ uint32_t mapa(uint32_t a, uint32_t r) {
  uint32_t o; asm volatile("mapa.shared::cluster.u32 %0, %1, %2;" : "=r"(o) : "r"(a), "r"(r)); return o;
}
__device__ __forceinline__ void mbar_init(uint32_t bar, uint32_t cnt) {
  asm volatile("mbarrier.init.shared::cta.b64 [%0], %1;" :: "r"(bar), "r"(cnt) : "memory");
}
__device__ __forceinline__ void mbar_arrive(uint32_t bar) {
  asm volatile("mbarrier.arrive.shared::cta.b64 _, [%0];" :: "r"(bar) : "memory");
}
__device__ __forceinline__ void mbar_expect(uint32_t bar, uint32_t bytes) {
  asm volatile("mbarrier.arrive.expect_tx.shared::cta.b64 _, [%0], %1;" :: "r"(bar), "r"(bytes) : "memory");
}
__device__ __forceinline__ bool mbar_try(uint32_t bar, uint32_t parity) {
  uint32_t ok;
  asm volatile("{\n.reg .pred p;\nmbarrier.try_wait.parity.shared::cta.b64 p, [%1], %2;\nselp.u32 %0, 1, 0, p;\n}"
               : "=r"(ok) : "r"(bar), "r"(parity) : "memory");
  return ok != 0;
}
constexpr int SPIN_LIMIT = 1 << 15;
__device__ __forceinline__ void mbar_wait(uint32_t bar, uint32_t parity) {
#pragma unroll 1
  for (int i = 0; i < SPIN_LIMIT; i++) if (mbar_try(bar, parity)) break;
}
__device__ __forceinline__ void gwait(uint32_t bar, uint32_t parity) {
#pragma unroll 1
  for (int i = 0; i < (1 << 22); i++) if (mbar_try(bar, parity)) break;
}
__device__ __forceinline__ void fence_async() { asm volatile("fence.proxy.async.shared::cta;" ::: "memory"); }
__device__ __forceinline__ void bar_sync(int id, int n) { asm volatile("bar.sync %0, %1;" :: "r"(id), "r"(n) : "memory"); }
__device__ __forceinline__ void bar_arrive(int id, int n) { asm volatile("bar.arrive %0, %1;" :: "r"(id), "r"(n) : "memory"); }

__device__ __forceinline__ void tma_load2d(uint32_t dst, const CUtensorMap* tm, int c0, int c1, uint32_t bar) {
  asm volatile("cp.async.bulk.tensor.2d.shared::cluster.global.mbarrier::complete_tx::bytes [%0], [%1, {%3, %4}], [%2];"
               :: "r"(dst), "l"(tm), "r"(bar), "r"(c0), "r"(c1) : "memory");
}
__device__ __forceinline__ void tma_load3d_mc(uint32_t dst, const CUtensorMap* tm, int c0, int c1, int c2, uint32_t bar, uint16_t mask) {
  asm volatile("cp.async.bulk.tensor.3d.shared::cluster.global.mbarrier::complete_tx::bytes.multicast::cluster [%0], [%1, {%3, %4, %5}], [%2], %6;"
               :: "r"(dst), "l"(tm), "r"(bar), "r"(c0), "r"(c1), "r"(c2), "h"(mask) : "memory");
}
__device__ __forceinline__ void mbar_arrive_remote(uint32_t bar) {
  asm volatile("mbarrier.arrive.shared::cluster.b64 _, [%0];" :: "r"(bar) : "memory");
}
__device__ __forceinline__ uint32_t clk() { uint32_t t;
  asm volatile("mov.u32 %0, %%clock;" : "=r"(t) :: "memory")
; return t; }
__device__ __forceinline__ uint32_t phase_bad(const uint4& v, uint32_t ph) {
  uint32_t a, b;
  asm("lop3.b32 %0, %1, %2, %3, 0x7E;" : "=r"(a) : "r"(v.x), "r"(v.y), "r"(ph));
  asm("lop3.b32 %0, %1, %2, %3, 0x7E;" : "=r"(b) : "r"(v.z), "r"(v.w), "r"(ph));
  return (a | b) & 1u;
}
__device__ __forceinline__ bool has_zero(const uint4& v) { return min(min(v.x, v.y), min(v.z, v.w)) == 0; }
__device__ __forceinline__ uint32_t par(int s) { uint32_t r; asm volatile("and.b32 %0, %1, 1;" : "=r"(r) : "r"(s)); return r; }
__device__ __forceinline__ bool elect() {
  uint32_t p;
  asm volatile("{\n.reg .pred p;\nelect.sync _|p, 0xffffffff;\nselp.u32 %0, 1, 0, p;\n}" : "=r"(p));
  return p != 0;
}
__device__ __forceinline__ int rd_head() { int v; asm volatile("mov.u32 %0, %%ctaid.y;" : "=r"(v)); return v; }
__device__ __forceinline__ int rd_rank() { int v; asm volatile("mov.u32 %0, %%ctaid.x;" : "=r"(v)); return v; }
template <typename T> __device__ __forceinline__ void pin(T& v) {
  if constexpr (sizeof(T) == 8) asm volatile("" : "+l"(v)); else asm volatile("" : "+r"(v));
}
__device__ __forceinline__ int opaque(int t) { asm volatile("" : "+r"(t)); return t; }
#define otid() opaque(tid)
__device__ __forceinline__ float ex2(float x) { float y; asm("ex2.approx.ftz.f32 %0, %1;" : "=f"(y) : "f"(x)); return y; }
__device__ __forceinline__ float rcp(float x) { float y; asm("rcp.approx.ftz.f32 %0, %1;" : "=f"(y) : "f"(x)); return y; }
__device__ __forceinline__ void tma_prefetch2d(const CUtensorMap* tm, int c0, int c1) {
  asm volatile("cp.async.bulk.prefetch.tensor.2d.L2.global [%0, {%1, %2}];" :: "l"(tm), "r"(c0), "r"(c1) : "memory");
}
__device__ __forceinline__ void tma_store2d(const CUtensorMap* tm, uint32_t src, int c0, int c1) {
  asm volatile("cp.async.bulk.tensor.2d.global.shared::cta.bulk_group [%0, {%2, %3}], [%1];"
               :: "l"(tm), "r"(src), "r"(c0), "r"(c1) : "memory");
}
__device__ __forceinline__ void bulk_commit() { asm volatile("cp.async.bulk.commit_group;" ::: "memory"); }
__device__ __forceinline__ void bulk_wait_read0() { asm volatile("cp.async.bulk.wait_group.read 0;" ::: "memory"); }
__device__ __forceinline__ void bulk_wait0() { asm volatile("cp.async.bulk.wait_group 0;" ::: "memory"); }
__device__ __forceinline__ void bulk_s2c(uint32_t dst, uint32_t src, uint32_t bytes, uint32_t bar) {
  asm volatile("cp.async.bulk.shared::cluster.shared::cta.mbarrier::complete_tx::bytes [%0], [%1], %2, [%3];"
               :: "r"(dst), "r"(src), "r"(bytes), "r"(bar) : "memory");
}
__device__ __forceinline__ void st_async32(uint32_t dst, uint32_t v, uint32_t bar) {
  asm volatile("st.async.shared::cluster.mbarrier::complete_tx::bytes.u32 [%0], %1, [%2];" :: "r"(dst), "r"(v), "r"(bar) : "memory");
}
__device__ __forceinline__ void sts32(uint32_t a, uint32_t v) { asm volatile("st.shared.u32 [%0], %1;" :: "r"(a), "r"(v) : "memory"); }
__device__ __forceinline__ void sts128(uint32_t a, uint4 v) {
  asm volatile("st.shared.v4.u32 [%0], {%1,%2,%3,%4};" :: "r"(a), "r"(v.x), "r"(v.y), "r"(v.z), "r"(v.w) : "memory");
}
__device__ __forceinline__ uint4 ld_relaxed128(const void* p) {
  uint4 v;
  asm volatile("ld.relaxed.gpu.global.v4.u32 {%0,%1,%2,%3}, [%4];" : "=r"(v.x), "=r"(v.y), "=r"(v.z), "=r"(v.w) : "l"(p) : "memory");
  return v;
}
__device__ __forceinline__ void st_relaxed128(void* p, uint32_t a, uint32_t b, uint32_t c, uint32_t d) {
  asm volatile("st.relaxed.gpu.global.v4.u32 [%0], {%1,%2,%3,%4};" :: "l"(p), "r"(a), "r"(b), "r"(c), "r"(d) : "memory");
}
__device__ __forceinline__ void st_relaxed64(void* p, uint32_t a, uint32_t b) {
  asm volatile("st.relaxed.gpu.global.v2.u32 [%0], {%1,%2};" :: "l"(p), "r"(a), "r"(b) : "memory");
}
__device__ __forceinline__ uint32_t nz(uint32_t w) { return w == 0 ? 0x80000000u : w; }
__device__ __forceinline__ float bf_lo(uint32_t w) { return __uint_as_float(w << 16); }
__device__ __forceinline__ float bf_hi(uint32_t w) { return __uint_as_float(w & 0xFFFF0000u); }
__device__ __forceinline__ void st_relaxed32(void* p, uint32_t a) {
  asm volatile("st.relaxed.gpu.global.u32 [%0], %1;" :: "l"(p), "r"(a) : "memory");
}
__device__ __forceinline__ uint32_t pack_bf16(float lo, float hi) {
  uint32_t r; asm("cvt.rn.bf16x2.f32 %0, %1, %2;" : "=r"(r) : "f"(hi), "f"(lo)); return r;
}
__device__ __forceinline__ void ldsm4_t(uint32_t* r, uint32_t addr) {
  asm volatile("ldmatrix.sync.aligned.m8n8.x4.trans.shared.b16 {%0,%1,%2,%3}, [%4];"
               : "=r"(r[0]), "=r"(r[1]), "=r"(r[2]), "=r"(r[3]) : "r"(addr) : "memory");
}
__device__ __forceinline__ void ldsm4(uint32_t* r, uint32_t addr) {
  asm volatile("ldmatrix.sync.aligned.m8n8.x4.shared.b16 {%0,%1,%2,%3}, [%4];"
               : "=r"(r[0]), "=r"(r[1]), "=r"(r[2]), "=r"(r[3]) : "r"(addr) : "memory");
}
__device__ __forceinline__ void mma16816(float* d, const uint32_t* a, uint32_t b0, uint32_t b1) {
  asm volatile("mma.sync.aligned.m16n8k16.row.col.f32.bf16.bf16.f32 {%0,%1,%2,%3}, {%4,%5,%6,%7}, {%8,%9}, {%0,%1,%2,%3};"
               : "+f"(d[0]), "+f"(d[1]), "+f"(d[2]), "+f"(d[3]) : "r"(a[0]), "r"(a[1]), "r"(a[2]), "r"(a[3]), "r"(b0), "r"(b1));
}
__device__ __forceinline__ void mma1688(float* d, uint32_t a0, uint32_t a1, uint32_t b0) {
  asm volatile("mma.sync.aligned.m16n8k8.row.col.f32.bf16.bf16.f32 {%0,%1,%2,%3}, {%4,%5}, {%6}, {%0,%1,%2,%3};"
               : "+f"(d[0]), "+f"(d[1]), "+f"(d[2]), "+f"(d[3]) : "r"(a0), "r"(a1), "r"(b0));
}
__device__ __forceinline__ void lds128(uint32_t* r, uint32_t addr) {
  asm volatile("ld.shared.v4.u32 {%0,%1,%2,%3}, [%4];" : "=r"(r[0]), "=r"(r[1]), "=r"(r[2]), "=r"(r[3]) : "r"(addr) : "memory");
}
__device__ __forceinline__ void stsm4_t(uint32_t addr, uint32_t a, uint32_t b, uint32_t c, uint32_t d) {
  asm volatile("stmatrix.sync.aligned.m8n8.x4.trans.shared.b16 [%0], {%1,%2,%3,%4};" :: "r"(addr), "r"(a), "r"(b), "r"(c), "r"(d) : "memory");
}
__device__ __forceinline__ void stsm4(uint32_t addr, uint32_t a, uint32_t b, uint32_t c, uint32_t d) {
  asm volatile("stmatrix.sync.aligned.m8n8.x4.shared.b16 [%0], {%1,%2,%3,%4};" :: "r"(addr), "r"(a), "r"(b), "r"(c), "r"(d) : "memory");
}
__device__ __forceinline__ uint32_t movm_t(uint32_t a) {
  uint32_t d; asm volatile("movmatrix.sync.aligned.m8n8.trans.b16 %0, %1;" : "=r"(d) : "r"(a)); return d;
}

struct Desc { uint32_t base, off, hi; };
__device__ __forceinline__ Desc mkd(uint32_t base, uint32_t boff, uint32_t lbo, uint32_t sbo, uint32_t swz) {
  return Desc{base, (boff >> 4) + ((lbo >> 4) << 16), (sbo >> 4) | (swz << 30)};
}
#define WG_FENCE() asm volatile("wgmma.fence.sync.aligned;" ::: "memory")
#define WG_COMMIT() asm volatile("wgmma.commit_group.sync.aligned;" ::: "memory")
#define WG_WAIT(n) asm volatile("wgmma.wait_group.sync.aligned " #n ";" ::: "memory")

#define ZERO(a, n) _Pragma("unroll") for (int _i = 0; _i < n; _i++) a[_i] = 0.f
#define F4(d, o) "+f"(d[o]), "+f"(d[o + 1]), "+f"(d[o + 2]), "+f"(d[o + 3])
#define F16(d, o) F4(d, o), F4(d, o + 4), F4(d, o + 8), F4(d, o + 12)
#define F64(d, o) F16(d, o), F16(d, o + 16), F16(d, o + 32), F16(d, o + 48)

template <int TB> __device__ __forceinline__ void wg_rs8(float* d, const uint32_t* a, Desc b, int sc) {
  asm volatile("{\n.reg .pred p;\n.reg .b32 lb;\n.reg .b64 db;\nsetp.ne.b32 p, %11, 0;\nadd.u32 lb, %8, %9;\nmov.b64 db, {lb, %10};\n"
               "wgmma.mma_async.sync.aligned.m64n8k16.f32.bf16.bf16 {%0,%1,%2,%3}, {%4,%5,%6,%7}, db, p, 1, 1, %12;\n}"
               : F4(d, 0) : "r"(a[0]), "r"(a[1]), "r"(a[2]), "r"(a[3]), "r"(b.base), "r"(b.off), "r"(b.hi), "r"(sc), "n"(TB));
}
template <int TA, int TB> __device__ __forceinline__ void wg_ss8(float* d, Desc a, Desc b, int sc) {
  asm volatile("{\n.reg .pred p;\n.reg .b32 la, lb;\n.reg .b64 da, db;\nsetp.ne.b32 p, %10, 0;\n"
               "add.u32 la, %4, %5;\nmov.b64 da, {la, %6};\nadd.u32 lb, %7, %8;\nmov.b64 db, {lb, %9};\n"
               "wgmma.mma_async.sync.aligned.m64n8k16.f32.bf16.bf16 {%0,%1,%2,%3}, da, db, p, 1, 1, %11, %12;\n}"
               : F4(d, 0) : "r"(a.base), "r"(a.off), "r"(a.hi), "r"(b.base), "r"(b.off), "r"(b.hi), "r"(sc), "n"(TA), "n"(TB));
}
template <int TB> __device__ __forceinline__ void wg_rs32(float* d, const uint32_t* a, Desc b, int sc) {
  asm volatile("{\n.reg .pred p;\n.reg .b32 lb;\n.reg .b64 db;\nsetp.ne.b32 p, %23, 0;\nadd.u32 lb, %20, %21;\nmov.b64 db, {lb, %22};\n"
               "wgmma.mma_async.sync.aligned.m64n32k16.f32.bf16.bf16 {%0,%1,%2,%3,%4,%5,%6,%7,%8,%9,%10,%11,%12,%13,%14,%15}, {%16,%17,%18,%19}, db, p, 1, 1, %24;\n}"
               : F16(d, 0) : "r"(a[0]), "r"(a[1]), "r"(a[2]), "r"(a[3]), "r"(b.base), "r"(b.off), "r"(b.hi), "r"(sc), "n"(TB));
}
template <int TA, int TB> __device__ __forceinline__ void wg_ss32(float* d, Desc a, Desc b, int sc) {
  asm volatile("{\n.reg .pred p;\n.reg .b32 la, lb;\n.reg .b64 da, db;\nsetp.ne.b32 p, %22, 0;\n"
               "add.u32 la, %16, %17;\nmov.b64 da, {la, %18};\nadd.u32 lb, %19, %20;\nmov.b64 db, {lb, %21};\n"
               "wgmma.mma_async.sync.aligned.m64n32k16.f32.bf16.bf16 {%0,%1,%2,%3,%4,%5,%6,%7,%8,%9,%10,%11,%12,%13,%14,%15}, da, db, p, 1, 1, %23, %24;\n}"
               : F16(d, 0) : "r"(a.base), "r"(a.off), "r"(a.hi), "r"(b.base), "r"(b.off), "r"(b.hi), "r"(sc), "n"(TA), "n"(TB));
}
template <int TA, int TB> __device__ __forceinline__ void wg_ss40(float* d, Desc a, Desc b, int sc) {
  asm volatile("{\n.reg .pred p;\n.reg .b32 la, lb;\n.reg .b64 da, db;\nsetp.ne.b32 p, %26, 0;\n"
               "add.u32 la, %20, %21;\nmov.b64 da, {la, %22};\nadd.u32 lb, %23, %24;\nmov.b64 db, {lb, %25};\n"
               "wgmma.mma_async.sync.aligned.m64n40k16.f32.bf16.bf16 {%0,%1,%2,%3,%4,%5,%6,%7,%8,%9,%10,%11,%12,%13,%14,%15,%16,%17,%18,%19}, da, db, p, 1, 1, %27, %28;\n}"
               : F16(d, 0), F4(d, 16) : "r"(a.base), "r"(a.off), "r"(a.hi), "r"(b.base), "r"(b.off), "r"(b.hi), "r"(sc), "n"(TA), "n"(TB));
}
template <int TA, int TB> __device__ __forceinline__ void wg_ss128(float* d, Desc a, Desc b, int sc) {
  asm volatile("{\n.reg .pred p;\n.reg .b32 la, lb;\n.reg .b64 da, db;\nsetp.ne.b32 p, %70, 0;\n"
               "add.u32 la, %64, %65;\nmov.b64 da, {la, %66};\nadd.u32 lb, %67, %68;\nmov.b64 db, {lb, %69};\n"
               "wgmma.mma_async.sync.aligned.m64n128k16.f32.bf16.bf16 {%0,%1,%2,%3,%4,%5,%6,%7,%8,%9,%10,%11,%12,%13,%14,%15,%16,%17,%18,%19,%20,%21,%22,%23,%24,%25,%26,%27,%28,%29,%30,%31,%32,%33,%34,%35,%36,%37,%38,%39,%40,%41,%42,%43,%44,%45,%46,%47,%48,%49,%50,%51,%52,%53,%54,%55,%56,%57,%58,%59,%60,%61,%62,%63}, da, db, p, 1, 1, %71, %72;\n}"
               : F64(d, 0) : "r"(a.base), "r"(a.off), "r"(a.hi), "r"(b.base), "r"(b.off), "r"(b.hi), "r"(sc), "n"(TA), "n"(TB));
}
template <int TA, int TB> __device__ __forceinline__ void wg_ss256(float* d, Desc a, Desc b, int sc) {
  asm volatile("{\n.reg .pred p;\n.reg .b32 la, lb;\n.reg .b64 da, db;\nsetp.ne.b32 p, %134, 0;\n"
               "add.u32 la, %128, %129;\nmov.b64 da, {la, %130};\nadd.u32 lb, %131, %132;\nmov.b64 db, {lb, %133};\n"
               "wgmma.mma_async.sync.aligned.m64n256k16.f32.bf16.bf16 {%0,%1,%2,%3,%4,%5,%6,%7,%8,%9,%10,%11,%12,%13,%14,%15,%16,%17,%18,%19,%20,%21,%22,%23,%24,%25,%26,%27,%28,%29,%30,%31,%32,%33,%34,%35,%36,%37,%38,%39,%40,%41,%42,%43,%44,%45,%46,%47,%48,%49,%50,%51,%52,%53,%54,%55,%56,%57,%58,%59,%60,%61,%62,%63,%64,%65,%66,%67,%68,%69,%70,%71,%72,%73,%74,%75,%76,%77,%78,%79,%80,%81,%82,%83,%84,%85,%86,%87,%88,%89,%90,%91,%92,%93,%94,%95,%96,%97,%98,%99,%100,%101,%102,%103,%104,%105,%106,%107,%108,%109,%110,%111,%112,%113,%114,%115,%116,%117,%118,%119,%120,%121,%122,%123,%124,%125,%126,%127}, da, db, p, 1, 1, %135, %136;\n}"
               : F64(d, 0), F64(d, 64) : "r"(a.base), "r"(a.off), "r"(a.hi), "r"(b.base), "r"(b.off), "r"(b.hi), "r"(sc), "n"(TA), "n"(TB));
}

constexpr int NRSC = 11;
#define GCH 9
#define KVB 4096
#define PRO_FIRST 1
#define F_G2 1
#define F_TID 1
#define F_SPREAD 0
#define PCH 99
#define B9J 8
#define QCH 2
#define NUE 2
#define NLE 3
__host__ __device__ constexpr int rs_chunk(int i) { return i < NLE ? i : i + NUE; }
__host__ __device__ constexpr int u_chunk(int i) { return i < NUE ? i + NLE : i + 7; }
__host__ __device__ constexpr bool is_u(int ch) { return (ch >= NLE && ch < NLE + NUE) || ch >= 7 + NUE; }
__host__ __device__ constexpr int pos_chunk(int p) { return p < 7 ? rs_chunk(p) : (p < 11 ? u_chunk(p - 7) : p); }
__host__ __device__ constexpr int cls_idx(int ch) { return is_u(ch) ? (ch < 7 + NUE ? ch - NLE : ch - 7) : (ch < NLE ? ch : ch - NUE); }
constexpr uint32_t R_SS = 0;
constexpr uint32_t R_POOL = 81920;
constexpr uint32_t R_MRS = R_POOL + 25600;
constexpr uint32_t R_V = 118784;
constexpr uint32_t R_K = 129024;
constexpr uint32_t R_Q = 139264;
constexpr uint32_t R_WO = R_Q + 10240;
constexpr uint32_t R_W4 = R_WO + 65536;
constexpr uint32_t R_P0 = R_K + 8192;
constexpr uint32_t R_PX = R_Q + 5120;
constexpr uint32_t R_BAR = 231424;
constexpr uint32_t R_INV = R_BAR + 224;
constexpr uint32_t REC_SMEM = 231680;
enum { B_XFULL = 0, B_SSFULL = 4, B_XDONE = 5, B_PRO = 6, B_POOL = 8, B_QKV = 9, B_KVX = 10, B_TFREE = 11, B_WSS = 12, B_WO = 13, B_W0 = 14, B_XTILE = 17, B_PUB = 18, B_VX = 19, B_LPUB = 20, B_G0 = 21, B_G1 = 22, B_LRET = 23, B_SD = 7 };
#define SS_ISSUE 0

struct RecMaps { CUtensorMap w[3]; CUtensorMap wo; CUtensorMap wo_half; CUtensorMap x3; CUtensorMap x2; CUtensorMap x1; CUtensorMap ox; int tune[8]; };

#define PROF(i) do {} while (0)
#define PDUMP() do {} while (0)
#define PVAL(i, v) do {} while (0)
#define PSYNC() do {} while (0)
#define TUNE(i) kDelay[i]
__device__ constexpr int kDelay[8] = {1000, 120, 0, 1500, 0, 0, 850, 0};
#define DELAY(i) do { if (kDelay[i] > 0) { unsigned _t0 = clock(); while ((int)(clock() - _t0) < kDelay[i]) {} } } while (0)

__global__ void __cluster_dims__(3, 1, 1) __launch_bounds__(384, 1)
rec_kernel(const __grid_constant__ RecMaps maps, const __nv_bfloat16* __restrict__ mem0, const __nv_bfloat16* __restrict__ xg,
           const __nv_bfloat16* __restrict__ wog) {
  extern __shared__ __align__(1024) uint8_t smem[];
  const uint32_t sb = smem_u32(smem);
  const int tid = F_TID ? __shfl_sync(~0u, (int)threadIdx.x, threadIdx.x & 31) : opaque(threadIdx.x);
  const int wid = __shfl_sync(~0u, tid >> 5, 0), wg = wid >> 2, wp = wid & 3;
  const uint32_t s16 = (sb & 0x3FFFF) >> 4;
  const int h = blockIdx.y, c = blockIdx.x;
  const uint32_t bars = sb + R_BAR;
  auto BAR = [&](int i) { return bars + 8u * i; };
  const uint32_t sWo = sb + R_WO;

  if (tid == 0 && h == 0 && c == 0) TL(0);
  if (tid == 0) {
    for (int i = 0; i < 5; i++) mbar_init(BAR(B_XFULL + i), 1);
    mbar_init(BAR(B_XDONE), 24); mbar_init(BAR(B_XTILE), 24); mbar_init(BAR(B_PUB), 8); mbar_init(BAR(B_LPUB), 4); mbar_init(BAR(B_VX), c == 2 ? 9 : 1); mbar_init(BAR(B_PRO), 24); mbar_init(BAR(B_SD), 4); mbar_init(BAR(B_G0), 8); mbar_init(BAR(B_G1), 8); mbar_init(BAR(B_LRET), 4); mbar_init(BAR(B_POOL), 3);
    mbar_init(BAR(B_QKV), c == 2 ? 1 : 9); mbar_init(BAR(B_KVX), 1); mbar_init(BAR(B_TFREE), c == 0 ? 1 : 2);
    mbar_init(BAR(B_WSS), 1); mbar_init(BAR(B_WO), 1);
    for (int i = 0; i < 3; i++) mbar_init(BAR(B_W0 + i), 1);
    asm volatile("fence.mbarrier_init.release.cluster;" ::: "memory");
    fence_async();
    mbar_expect(BAR(B_W0 + 0), 81920); mbar_expect(BAR(B_W0 + 1), 32768); mbar_expect(BAR(B_W0 + 2), 65536);
  }
  if (h == 0 && c == 0 && tid < SY_N) { gSync[tid] = 0; __threadfence(); }
  __syncthreads();
  asm volatile("barrier.cluster.arrive.relaxed.aligned;" ::: "memory");
  asm volatile("griddepcontrol.launch_dependents;" ::: "memory");
  if ((tid & 31) == 0) {
    if (wid < NRSC) {
      const int i = wid;
      const int ch = i < 7 ? rs_chunk(i) : u_chunk(i - 7);
      const uint32_t dst = i < 5 ? sb + R_SS + i * 16384 : (i < 7 ? sb + R_POOL + (i - 5) * 16384 : sWo + (i - 7) * 8192);
      const uint32_t bar = BAR(B_W0 + (i < 5 ? 0 : (i < 7 ? 1 : 2)));
      tma_load2d(dst, &maps.w[c], h * 128, ch * 64, bar);
      tma_load2d(dst + (i < 7 ? 8192 : 32768), &maps.w[c], h * 128 + 64, ch * 64, bar);
    } else if (h * 3 + c < 8) {
      asm volatile("cp.async.bulk.prefetch.L2.global [%0], %1;" :: "l"(reinterpret_cast<const char*>(xg) + (h * 3 + c) * 32768), "r"(32768) : "memory");
    }
  }
  __syncwarp();
  asm volatile("barrier.cluster.wait.aligned;" ::: "memory");

  { constexpr int ROLE = 0; PROF(15); (void)ROLE; }

  const float sl2e = 0.08838834764831845f * 1.4426950408889634f;
  if (wg < 2) {
    asm volatile("setmaxnreg.inc.sync.aligned.u32 224;");
    constexpr int ROLE = 0; (void)ROLE;
    uint32_t wa[28 * 4], wo[16 * 4];
#pragma unroll
    for (int i = 0; i < 64; i++) wo[i] = 0;
    {
      const uint32_t fo = (((tid >> 4) & 1) * 8 + (tid & 7)) * 128 + (((wp * 2 + ((tid >> 3) & 1)) ^ (tid & 7)) << 4);
#pragma unroll
      for (int i = 0; i < 7; i++) {
        if (i % 5 == 0) mbar_wait(BAR(B_W0 + i / 5), 0);
        if (i == 0 && tid == 0 && h == 0 && c == 0) TL(5);
        const uint32_t src = (i < 5 ? sb + R_SS + i * 16384 : sb + R_POOL + (i - 5) * 16384) + wg * 8192 + fo;
#pragma unroll
        for (int j = 0; j < 4; j++) ldsm4_t(&wa[(i * 4 + j) * 4], src + j * 2048);
        if (i == 4) {
          bar_sync(3, 256);
          if (tid == 0) { fence_async(); mbar_expect(BAR(B_WSS), 81920); }
          if ((tid & 31) == 0 && wid >= 1 && wid < 6) {
            fence_async();
            for (int t = 0; t < 2; t++)
              tma_load2d(sb + R_SS + t * 40960 + (wid - 1) * 8192, &maps.w[c], h * 128 + t * 64, (NRSC + wid - 1) * 64, BAR(B_WSS));
          }
          __syncwarp();
        }
      }
      bar_sync(3, 256);
      if (tid == 0) {
        fence_async();
        mbar_arrive_remote(mapa(BAR(B_POOL), 0));
        mbar_expect(BAR(B_WO), c == 0 ? 16384 : 24576);
        tma_load2d(sb + R_W4, &maps.wo, (12 + c) * 64, h * 128, BAR(B_WO));
        if (c != 0) {
          tma_load2d(sb + R_Q, &maps.wo_half, 928 + c * 32, h * 128, BAR(B_WO));
          tma_load2d(sb + R_Q + 5120, &maps.wo_half, 928 + c * 32, h * 128 + 64, BAR(B_WO));
        }
      } else if (tid == 32) {
        for (int t = 0; t < 4; t++) tma_prefetch2d(&maps.wo, ((t >> 1) * 6 + c * 2 + (t & 1)) * 64, h * 128);
      } else if (tid == 64) {
        const uint32_t per = 40960;
        asm volatile("cp.async.bulk.prefetch.L2.global [%0], %1;" :: "l"(reinterpret_cast<const char*>(xg) + 262144 + (h * 3 + c) * per), "r"(per) : "memory");
      }
      __syncwarp();
    }
    mbar_wait(BAR(B_WSS), 0);
    mbar_wait(BAR(B_W0 + 2), 0);
    if (tid == 0 && h == 0 && c == 0) TL(6);
    const uint32_t aSS = s16 + (R_SS >> 4) + wg * 2560;
    const uint32_t aU = s16 + (R_WO >> 4) + wg * 2048;
#define TBASE (R_Q - rd_rank() * 10240)
    PROF(0);
    if (tid == 0 && h == 0 && c == 0) TL(1);
    if (tid == 4) mbar_expect(BAR(B_SSFULL), 20480);
    __syncwarp();
    uint32_t ma = 0;

#pragma unroll 1
    for (int s = -1; s < NSEG; s++) {
      float mr[4];
      ZERO(mr, 4);
      if (s >= 0) {
        float am[12];
        ZERO(am, 12);
        uint32_t bf[4][4];
#pragma unroll
        for (int j = 0; j < 3; j++) ldsm4(bf[j], (ma ^ ((j & 1) << 6)) + (j >> 1) * 1024);
#pragma unroll
        for (int j = 0; j < 14; j++) {
          if (j + 3 < 14) ldsm4(bf[(j + 3) & 3], (ma ^ (((j + 3) & 1) << 6)) + ((j + 3) >> 1) * 1024);
          mma16816((j & 1) ? am + 4 : mr, &wa[j * 8], bf[j & 3][0], bf[j & 3][1]);
          mma16816((j & 1) ? am + 8 : am, &wa[j * 8 + 4], bf[j & 3][2], bf[j & 3][3]);
        }
#pragma unroll
        for (int e = 0; e < 4; e++) mr[e] = (mr[e] + am[e]) + (am[4 + e] + am[8 + e]);
        PROF(8);
        if (F_G2) mbar_wait(BAR(B_G1), s & 1);
      }
      PROF(1);
      float a40[20];
      ZERO(a40, 16);
#pragma unroll
      for (int e = 0; e < 4; e++) a40[16 + e] = mr[e];
      float au[4];
      ZERO(au, 4);
      WG_FENCE();
#pragma unroll
      for (int j = 0; j < 16; j++)
        wg_ss8<1, 0>(au, mkd(aU, j * 2048, 0, 1024, 1), mkd(s16, R_MRS + (7 + (j >> 2)) * 1024 + (j & 3) * 32, 0, 1024, 1), 1);
      WG_COMMIT();
      if (s + 1 < NSEG) mbar_wait(BAR(B_SSFULL), (s + 1) & 1);
      WG_FENCE();
#pragma unroll
      for (int j = 0; j < 20; j++)
        wg_ss40<1, 0>(a40, mkd(aSS, j * 2048, 0, 1024, 1), mkd(s16, R_POOL + (j >> 2) * 5120 + (j & 3) * 32, 0, 1024, 1), 1);
      WG_COMMIT();
      uint32_t o0, o1, o2, rb0, rb1, rb2, probar;
      {
        const int ln = otid() & 31, tok = ln >> 2, rk = rd_rank();
        o0 = sb + R_Q - rk * 10240 + wg * 5120 + 4096 + tok * 128 + (((wp * 2) ^ tok) << 4) + (ln & 3) * 4;
        const uint32_t r1 = rk == 2 ? 0 : rk + 1, r2 = rk == 0 ? 2 : rk - 1;
        probar = ln < (F_SPREAD ? 3 : 1) ? mapa(BAR(B_PRO), ln) : 0;
        rb0 = rk == 2 ? BAR(B_VX) : BAR(B_QKV);
        o1 = mapa(o0, r1); o2 = mapa(o0, r2); rb1 = mapa(rb0, r1); rb2 = mapa(rb0, r2);
      }
      WG_WAIT(0);
      if (s + 1 < NSEG && probar != 0) mbar_arrive_remote(probar);
      float ax[16];
#pragma unroll
      for (int e = 0; e < 16; e++) ax[e] = a40[e];
      if (s >= 0) {
        PROF(2);
        const uint32_t m0 = movm_t(pack_bf16(a40[16] + au[0], a40[17] + au[1]));
        const uint32_t m1 = movm_t(pack_bf16(a40[18] + au[2], a40[19] + au[3]));
        st_async32(o1, m0, rb1);
        st_async32(o2, m0, rb2);
        st_async32(o1 ^ 16, m1, rb1);
        st_async32(o2 ^ 16, m1, rb2);
        sts32(o0, m0);
        sts32(o0 ^ 16, m1);
        __syncwarp();
        if (elect()) mbar_arrive(rb0);
      }
      if (s == NSEG - 1) break;
      if (tid < 5 && (tid < 4 || s + 2 < NSEG)) mbar_expect(BAR(B_XFULL + tid), tid < 3 ? 12288 : (tid == 3 ? 8192 : 20480));
      if (tid == 224 && (F_SPREAD || rd_rank() == 0)) {
        mbar_wait(BAR(B_PRO), (s + 1) & 1);
        for (int j = F_SPREAD ? rd_rank() : 0; j < 3; j += F_SPREAD ? 3 : 1)
          tma_load3d_mc(sb + R_POOL + j * 12288, &maps.x3, 0, (s + 1) * SEG, j * 3, BAR(B_XFULL + j), 7);
      }
      __syncwarp();
      if (s <= 0) {
        const int t = otid();
        const uint2* wp0 = reinterpret_cast<const uint2*>(wog + (size_t)(rd_head() * 128 + ((t & 31) >> 2)) * DM + (rd_rank() * 2 + wg) * 64 + wp * 16) + (t & 3);
        if (s < 0) {
#pragma unroll
          for (int i = 0; i < 16; i++) { const uint2 u = __ldg(wp0 + i * 8 * (DM / 4)); wo[2 * i] = u.x; wo[2 * i + 1] = u.y; }
        } else {
#pragma unroll
          for (int i = 0; i < 16; i++) { const uint2 u = __ldg(wp0 + i * 8 * (DM / 4) + 96); wo[32 + 2 * i] = u.x; wo[33 + 2 * i] = u.y; }
#pragma unroll
          for (int i = 0; i < 64; i++) wo[i] = movm_t(wo[i]);
        }
      }
      if (s >= 0) {
        PROF(3);
        PDUMP();
        const int ln = otid() & 31;
        uint32_t pdst = (((s & 1) * 64 + rd_rank() * 8 + wg * 4 + wp) * 32 + rd_head()) * 256 + ((ln & 3) * 8 + (ln >> 2)) * 8;
        uint32_t oa = sb + R_Q + 4096 + ln * 16;
        pin(pdst); pin(oa);
        if (wid == 6) {
          mbar_wait(BAR(B_SD), s & 1);
          const int rk = rd_rank();
          if (tid == 192 && rk != 0) tma_load3d_mc(sb + R_K, &maps.x2, 0, (s + 1) * SEG, 9, BAR(B_XFULL + 3), (uint16_t)(1 << rk));
          __syncwarp();
        }
        bar_sync(7, 384);
        uint32_t ob[2][4];
        lds128(ob[0], oa);
        lds128(ob[1], oa + 512);
        float a0[4], a1[4];
        ZERO(a0, 4); ZERO(a1, 4);
#pragma unroll
        for (int i = 0; i < 4; i++) {
          mma16816(a0, &wo[i * 8], ob[i & 1][0], ob[i & 1][1]);
          mma16816(a1, &wo[32 + i * 8], ob[i & 1][0], ob[i & 1][1]);
          mma16816(a0, &wo[i * 8 + 4], ob[i & 1][2], ob[i & 1][3]);
          mma16816(a1, &wo[32 + i * 8 + 4], ob[i & 1][2], ob[i & 1][3]);
          if (i < 2) lds128(ob[i & 1], oa + 5120 + i * 512);
        }
        char* pd = reinterpret_cast<char*>(gPart) + pdst;
        st_relaxed64(pd, nz(pack_bf16(a0[0], a0[1])), nz(pack_bf16(a0[2], a0[3])));
        st_relaxed64(pd + 24 * 8192, nz(pack_bf16(a1[0], a1[1])), nz(pack_bf16(a1[2], a1[3])));
        PROF(4);
        mbar_wait(BAR(B_XFULL), (s + 1) & 1);
        bar_sync(9, 384);
        PROF(5);
        DELAY(4);
      }
      uint4 v[4];
      const uint4* src = gMem + ((rd_head() & (NREP - 1)) * 4 + ((s + 1) & 3)) * 1024 + otid();
#pragma unroll
      for (int ch = 0; ch < NRSC; ch++) {
        if (ch % 3 == 0 && (ch > 0 || s < 0)) mbar_wait(BAR(B_XFULL + ch / 3), (s + 1) & 1);
        if (ch == 0) { PROF(13); } else if (ch == 9) { PROF(14); }
        if (ch == PCH && s >= 0 && rd_rank() != 0) mbar_wait(BAR(B_LRET), s & 1);
        if (ch == 7 + NUE) {
          if ((tid & 127) == 96 && s + 2 < NSEG) {
            const int j = rd_rank() * 2 + wg - 1;
            if (j >= 0) {
              mbar_wait(BAR(B_XTILE), (s + 1) & 1);
              DELAY(5);
              tma_load3d_mc(sb + R_POOL + j * 5120, &maps.x1, 0, (s + 2) * SEG, NRSC + j, BAR(B_SSFULL), 7);
            }
          }
          __syncwarp();
          if (s >= 0 && rd_rank() != 0) mbar_wait(BAR(B_LPUB), s & 1);
        }
        if (ch % 3 == 0 || ch == 7 + NUE || ch == GCH + 1 || ch == 7 || ch == PCH) WG_FENCE();
#pragma unroll
        for (int j = 0; j < 4; j++)
        {
          const Desc db = mkd(s16, (ch < 9 ? R_POOL + ch * 4096 : R_K + (ch - 9) * 4096) + j * 32, 0, 1024, 1);
#define XSKIP 0
          if (is_u(ch)) { if (XSKIP < 1) wg_ss32<1, 0>(ax, mkd(aU, (cls_idx(ch) * 4 + j) * 2048, 0, 1024, 1), db, 1); }
          else if (XSKIP < 2 || ch == 0) wg_rs32<0>(ax, &wa[(cls_idx(ch) * 4 + j) * 4], db, 1);
        }
        if (ch % 3 == 2 || ch == 10 || ch == 6 + NUE || ch == GCH || ch == 6 || ch == PCH - 1) WG_COMMIT();
        if (ch == 6) {
          WG_WAIT(1);
          { const int ln = otid() & 31; if (ln < 3) mbar_arrive_remote(mapa(BAR(B_XTILE), ln)); }
        }
        if (ch == GCH) {
          if (s >= 0) {
            mbar_wait(BAR(B_PUB), s & 1);
            DELAY(1);
            PROF(10);
#pragma unroll
            for (int i = 0; i < 4; i++) v[i] = ld_relaxed128(src + i * 256);
          } else {
            const int t = otid(), n = (t >> 3) & 7;
#pragma unroll
            for (int i = 0; i < 4; i++) v[i] = *reinterpret_cast<const uint4*>(mem0 + n * DM + pos_chunk(i * 4 + (t >> 6)) * 64 + ((t & 7) ^ n) * 8);
          }
        }
      }
      WG_WAIT(0);
      { const int ln = otid() & 31; if (ln < 3) mbar_arrive_remote(mapa(BAR(B_XDONE), ln)); }
      PROF(6);
      if (s >= 0 && rd_rank() == 0) mbar_wait(BAR(B_TFREE), s & 1);
      bar_sync(3, 256);
      {
        const int ln = otid() & 31, r = ln & 7, blk = ln >> 3;
        const uint32_t ta = sb + TBASE + wg * 5120 + ((blk >> 1) * 8 + r) * 128 + (((wp * 2 + (blk & 1)) ^ r) << 4);
#pragma unroll
        for (int jj = 0; jj < 2; jj++)
          stsm4_t(ta + jj * 2048, pack_bf16(ax[jj * 8 + 0], ax[jj * 8 + 1]), pack_bf16(ax[jj * 8 + 2], ax[jj * 8 + 3]),
                  pack_bf16(ax[jj * 8 + 4], ax[jj * 8 + 5]), pack_bf16(ax[jj * 8 + 6], ax[jj * 8 + 7]));
      }
      PROF(7);
      {
        const int t = otid();
        const uint32_t q = wid >> 1;
        uint32_t d0 = sb + R_MRS + t * 16;
        uint32_t d2 = q == 3 ? d0 - (R_MRS + 3072) + R_POOL + 4096 : d0 + 8192;
        uint32_t d3 = d0 - R_MRS + R_POOL + 5120 + 4096 + q * 4096;
        ma = sb + R_MRS + (t & 7) * 128 + ((((t >> 3) & 3) ^ (t & 7)) << 4);
        pin(d0); pin(d2); pin(d3); pin(ma);
#pragma unroll
        for (int hf = 0; hf < 2; hf++) {
#pragma unroll 1
          for (int it = s >= 0 ? 0 : SPIN_LIMIT - 1; it < SPIN_LIMIT; it++) {
            uint32_t mn[2];
#pragma unroll
            for (int i = 0; i < 2; i++) {
              const uint4 u = v[hf * 2 + i];
              mn[i] = min(min(u.x, u.y), min(u.z, u.w));
              sts128(hf == 0 ? d0 + i * 4096 : (i == 0 ? d2 : d3), u);
              if (mn[i] == 0) v[hf * 2 + i] = ld_relaxed128(src + (hf * 2 + i) * 256);
            }
            if (__all_sync(~0u, min(mn[0], mn[1]) != 0)) break;
            if (hf == 0) {
#pragma unroll
              for (int i = 2; i < 4; i++) if (has_zero(v[i])) v[i] = ld_relaxed128(src + i * 256);
            }
          }
          if (hf == 0) { PROF(11); if (F_G2 && elect()) mbar_arrive(BAR(B_G0)); }
        }
      }
      fence_async();
      PROF(9);
      if (F_G2) { __syncwarp(); if (elect()) mbar_arrive(BAR(B_G1)); }
      bar_arrive(1, 288);
      if (F_G2) mbar_wait(BAR(B_G0), (s + 1) & 1); else bar_sync(3, 256);
    }
  } else {
    asm volatile("setmaxnreg.dec.sync.aligned.u32 56;");
    constexpr int ROLE = 1; (void)ROLE;
    if (tid == 256) {
      mbar_expect(BAR(B_QKV), c == 2 ? 4096 : 2048);
      mbar_expect(BAR(B_KVX), c == 1 ? 0 : 2 * KVB);
      mbar_expect(BAR(B_VX), c == 2 ? 0 : 2048 + 2 * KVB);
    }
    if (c == 0 && tid == 352) {
      mbar_wait(BAR(B_POOL), 0);
      for (int j = 0; j < 5; j++) tma_load3d_mc(sb + R_POOL + j * 5120, &maps.x1, 0, 0, NRSC + j, BAR(B_SSFULL), 7);
      tma_load3d_mc(sb + R_K, &maps.x2, 0, 0, 9, BAR(B_XFULL + 3), 7);
    }
    __syncwarp();
    mbar_wait(BAR(B_WO), 0);
    auto ARM = [&]() {
        if (tid == 352) {
          const int rk = rd_rank();
          mbar_expect(BAR(B_QKV), rk == 2 ? 4096 : 2048);
          mbar_expect(BAR(B_KVX), rk == 1 ? 0 : 2 * KVB);
          mbar_expect(BAR(B_VX), rk == 2 ? 0 : 2048 + 2 * KVB);
          if (rk == 1) mbar_arrive_remote(mapa(BAR(B_TFREE), 2));
        }
        __syncwarp();
    };
#pragma unroll 1
    for (int s = 0; s < NSEG; s++) {
      if (wp == 3) {
        bar_sync(1, 288);
        if (tid < 356) {
          if (rd_rank() != 0) {
            mbar_wait(BAR(B_XDONE), par(s));
            if (s > 0 && rd_rank() == 2) mbar_wait(BAR(B_TFREE), par(s - 1));
            DELAY(2);
            const int t = otid(), c = rd_rank();
            const uint32_t src = sb + R_K + 10240 - c * 10240 + ((t >> 1) & 1) * 5120, r2 = (t & 1) == 0 ? 0u : (uint32_t)(3 - c);
            bulk_s2c(mapa(src, r2), src, KVB, mapa(c == 1 ? BAR(B_KVX) : BAR(B_VX), r2));
          }
        }
        __syncwarp();
      }
      PROF(2);
      PDUMP();
      if (s == 1 && tid == 256 && rd_head() == 0 && rd_rank() == 0) TL(2);
      if ((s & 15) == 8 && tid == 256 && rd_head() == 0 && rd_rank() == 0) TL(8 + (s >> 4));
      if (s > 0 && rd_rank() != 0) {
        if (wp != 3) DELAY(3);
        const int ln = otid() & 31;
        uint4* z = gPart + ((par(s + 1) * 64 + rd_head() * 2 + rd_rank() - 1) * 32 + (ln >> 2)) * 16 + wp * 4 + (ln & 3);
#pragma unroll
        for (int i = 0; i < 4; i++) st_relaxed128(z + i * 128, 0, 0, 0, 0);
      }
      const bool more = s + 1 < NSEG;
      uint32_t tref = 0;
      mbar_wait(BAR(B_KVX), par(s));
      if (more) {
        uint32_t vx, va, wad, had, po;
        {
          const int ln = otid() & 31;
          vx = sb + R_V + (wp >> 1) * 5120 + (ln & 15) * 128 + ((((wp & 1) * 4 + (ln >> 4)) ^ (ln & 7)) << 4);
          pin(vx);
          va = sb + R_V + (wp >> 1) * 5120 + 4096 + (ln & 7) * 128 + ((((wp & 1) * 4 + (ln >> 3)) ^ (ln & 7)) << 4);
          wad = sb + R_W4 + (((ln >> 4) & 1) * 8 + (ln & 7)) * 128 + (((wp * 2 + ((ln >> 3) & 1)) ^ (ln & 7)) << 4);
          had = sb + R_Q + (((ln >> 4) & 1) * 8 + (ln & 7)) * 64 + (((wp * 2 + ((ln >> 3) & 1)) ^ ((ln >> 1) & 3)) << 4);
          po = ((par(s) * 64 + 48 + rd_rank() * 4 + wp) * 32 + rd_head()) * 256 + ((ln & 3) * 8 + (ln >> 2)) * 8;
          pin(va); pin(wad); pin(had); pin(po);
        }
        mbar_wait(BAR(B_QKV), par(s));
        PROF(3);
        fence_async();
        float sc[20];
        ZERO(sc, 20);
        WG_FENCE();
#pragma unroll
        for (int j = 0; j < 8; j++) {
          Desc da = mkd(s16, R_Q + 4096 + (j >> 2) * 5120 + (j & 3) * 32, 0, 0, 1);
          Desc db = mkd(s16, R_K + (j >> 2) * 5120 + (j & 3) * 32, 0, 1024, 1);
          wg_ss40<0, 0>(sc, da, db, j > 0);
        }
        WG_COMMIT();
        mbar_wait(BAR(B_VX), par(s));
        WG_WAIT(0);
        PROF(4);
        if (elect()) mbar_arrive(BAR(B_SD));
        uint32_t vf[16], vm[4];
#pragma unroll
        for (int i = 0; i < 4; i++) ldsm4_t(vf + i * 4, (vx ^ ((i & 1) << 5)) + (i >> 1) * 2048);
        ldsm4_t(vm, va);
        float mx = fmaxf(fmaxf(fmaxf(sc[0], sc[1]), fmaxf(sc[4], sc[5])), fmaxf(fmaxf(sc[8], sc[9]), fmaxf(sc[12], sc[13])));
        mx = fmaxf(mx, fmaxf(sc[16], sc[17]));
        mx = fmaxf(mx, __shfl_xor_sync(~0u, mx, 1));
        mx = fmaxf(mx, __shfl_xor_sync(~0u, mx, 2));
        uint32_t pk[10];
#pragma unroll
        for (int j = 0; j < 5; j++) {
          pk[2 * j] = pack_bf16(ex2((sc[4 * j] - mx) * sl2e), ex2((sc[4 * j + 1] - mx) * sl2e));
          pk[2 * j + 1] = __float_as_uint(sc[(j >> 1) * 8 + (j & 1) * 2 + 1]);
        }
        uint32_t ones[2];
        asm volatile("mov.u32 %0, 0x3F803F80;" : "=r"(ones[0]));
        asm volatile("mov.u32 %0, 0x3F803F80;" : "=r"(ones[1]));
        PROF(10);
        float oc[20];
        ZERO(oc, 20);
#pragma unroll
        for (int t = 0; t < 2; t++) {
          mma16816(oc + 16, pk + 4 * t, ones[0], ones[1]);
#pragma unroll
          for (int n = 0; n < 4; n++) mma16816(oc + n * 4, pk + 4 * t, vf[t * 8 + n * 2], vf[t * 8 + n * 2 + 1]);
        }
        mma1688(oc + 16, pk[8], pk[9], ones[0]);
#pragma unroll
        for (int n = 0; n < 4; n++) mma1688(oc + n * 4, pk[8], pk[9], vm[n]);
        mbar_wait(BAR(B_SD), par(s));
        const float inv = rcp(oc[16]);
        const uint32_t oa = sb + R_Q + 4096 + (otid() & 31) * 16;
        sts128(oa + (wp >> 1) * 5120 + (wp & 1) * 512,
               make_uint4(pack_bf16(oc[0] * inv, oc[1] * inv), pack_bf16(oc[4] * inv, oc[5] * inv), pack_bf16(oc[8] * inv, oc[9] * inv), pack_bf16(oc[12] * inv, oc[13] * inv)));
        bar_arrive(7, 384);
        tref = clock() + (rd_rank() == 1 ? TUNE(0) : TUNE(6));
        const bool second = wp < 2 && rd_rank() != 0;
        uint32_t af[16], ob[2][4];
        float a0[4], a1[4];
        ZERO(a0, 4); ZERO(a1, 4);
        if (!second) {
#pragma unroll
          for (int j = 0; j < 4; j++) ldsm4_t(af + j * 4, wad + j * 2048);
          PROF(6);
          bar_sync(6, 128);
          lds128(ob[0], oa);
          lds128(ob[1], oa + 512);
#pragma unroll
          for (int j = 0; j < 8; j++) {
            mma16816((j & 1) ? a1 : a0, af + (j & 3) * 4, ob[(j >> 1) & 1][(j & 1) * 2], ob[(j >> 1) & 1][(j & 1) * 2 + 1]);
            if (j & 1) __syncwarp();
            if (j < 4) ldsm4_t(af + j * 4, wad + (j + 4) * 2048);
            if (j == 1 || j == 3) lds128(ob[j >> 1], oa + 5120 + (j >> 1) * 512);
          }
        } else {
          float a2[4], a3[4];
          ZERO(a2, 4); ZERO(a3, 4);
#pragma unroll
          for (int j = 0; j < 2; j++) { ldsm4_t(af + j * 8, wad + j * 2048); ldsm4_t(af + j * 8 + 4, had + j * 1024); }
          PROF(6);
          bar_sync(6, 128);
          lds128(ob[0], oa);
          lds128(ob[1], oa + 512);
#pragma unroll
          for (int j = 0; j < 8; j++) {
            const uint32_t b0 = ob[(j >> 1) & 1][(j & 1) * 2], b1 = ob[(j >> 1) & 1][(j & 1) * 2 + 1];
            mma16816((j & 1) ? a1 : a0, af + (j & 1) * 8, b0, b1);
            mma16816((j & 1) ? a3 : a2, af + (j & 1) * 8 + 4, b0, b1);
            if (j == B9J) bar_arrive(9, 384);
            __syncwarp();
            if (j + 2 < 8) {
              ldsm4_t(af + (j & 1) * 8, wad + (j + 2) * 2048);
              ldsm4_t(af + (j & 1) * 8 + 4, had + ((j + 2) >> 2) * 5120 + ((j + 2) & 3) * 1024);
            }
            if (j == 1 || j == 3) lds128(ob[j >> 1], oa + 5120 + (j >> 1) * 512);
          }
          st_relaxed64(reinterpret_cast<char*>(gPart) + po + (10 - rd_rank() * 2) * 8192, nz(pack_bf16(a2[0] + a3[0], a2[1] + a3[1])), nz(pack_bf16(a2[2] + a3[2], a2[3] + a3[3])));
        }
        st_relaxed64(reinterpret_cast<char*>(gPart) + po, nz(pack_bf16(a0[0] + a1[0], a0[1] + a1[1])), nz(pack_bf16(a0[2] + a1[2], a0[3] + a1[3])));
        if (rd_rank() != 0 && !(second && B9J < 8)) bar_arrive(9, 384);
      } else {
        mbar_wait(BAR(B_QKV), par(s));
        mbar_wait(BAR(B_VX), par(s));
      }
      PROF(12);
      if (rd_rank() == 0) {
        fence_async();
        {
          float sc[20];
          ZERO(sc, 20);
          WG_FENCE();
#pragma unroll
          for (int j = 0; j < 8; j++)
            wg_ss40<0, 0>(sc, mkd(s16, R_Q + (j >> 2) * 5120 + (j & 3) * 32, 0, 1024, 1), mkd(s16, R_K + (j >> 2) * 5120 + (j & 3) * 32, 0, 1024, 1), j > 0);
          WG_COMMIT();
          if (more) { bar_arrive(9, 384); ARM(); }
          WG_WAIT(0);
          bar_sync(6, 128);
          if (wp < 2) {
            const int ln = otid() & 31;
            const uint32_t pa = sb + R_PX + wp * 1536 + ln * 4;
            float mx[2], sum[2];
#pragma unroll
            for (int hf = 0; hf < 2; hf++) {
              const int lim = wp * 16 + hf * 8 + (ln >> 2) - (ln & 3) * 2;
              mx[hf] = -3.0e38f;
#pragma unroll
              for (int j = 0; j < 10; j++) {
                float& v = sc[(j >> 1) * 4 + hf * 2 + (j & 1)];
                v = (j >= 8 || (j >> 1) * 8 + (j & 1) <= lim) ? v * sl2e : -1.4426950408889634e9f;
                mx[hf] = fmaxf(mx[hf], v);
              }
            }
#pragma unroll
            for (int o = 1; o <= 2; o <<= 1) { mx[0] = fmaxf(mx[0], __shfl_xor_sync(~0u, mx[0], o)); mx[1] = fmaxf(mx[1], __shfl_xor_sync(~0u, mx[1], o)); }
#pragma unroll
            for (int hf = 0; hf < 2; hf++) {
              sum[hf] = 0.f;
#pragma unroll
              for (int j = 0; j < 10; j++) { float& v = sc[(j >> 1) * 4 + hf * 2 + (j & 1)]; v = ex2(v - mx[hf]); sum[hf] += v; }
            }
#pragma unroll
            for (int o = 1; o <= 2; o <<= 1) { sum[0] += __shfl_xor_sync(~0u, sum[0], o); sum[1] += __shfl_xor_sync(~0u, sum[1], o); }
#pragma unroll
            for (int hf = 0; hf < 2; hf++) {
              const float inv = rcp(sum[hf]);
#pragma unroll
              for (int j = 0; j < 5; j++) sts32(pa + hf * 768 + j * 128, pack_bf16(sc[j * 4 + hf * 2] * inv, sc[j * 4 + hf * 2 + 1] * inv));
              sts32(pa + hf * 768 + 640, 0);
            }
            fence_async();
          } else if (tid == 352 && more) {
            tma_load3d_mc(sb + R_K, &maps.x2, 0, (s + 1) * SEG, 9, BAR(B_XFULL + 3), 1);
          }
          __syncwarp();
        }
        bar_sync(6, 128);
        const int ln = otid() & 31, r = ln & 7, blk = ln >> 3;
        const uint32_t oa = sb + R_V + ((blk >> 1) * 8 + r) * 128 + (((wp * 2 + (blk & 1)) ^ r) << 4);
#pragma unroll
        for (int tl = 0; tl < 2; tl++) {
          float ox[16];
          ZERO(ox, 16);
          WG_FENCE();
#pragma unroll
          for (int j = 0; j < 3; j++)
            wg_ss32<1, 0>(ox, mkd(s16, R_V + tl * 5120 + j * 2048, 0, 1024, 1), mkd(s16, R_PX + j * 256, 128, 768, 0), j > 0);
          WG_COMMIT();
          WG_WAIT(0);
          bar_sync(6, 128);
          if (tl == 1 && more && tid == 288) mbar_arrive(BAR(B_TFREE));
#pragma unroll
          for (int jj = 0; jj < 2; jj++) {
            const float* a = ox + jj * 8;
            stsm4_t(oa + tl * 5120 + jj * 2048, pack_bf16(a[0], a[1]), pack_bf16(a[2], a[3]), pack_bf16(a[4], a[5]), pack_bf16(a[6], a[7]));
          }
        }
        fence_async();
        bar_sync(6, 128);
        if (tid == 256) {
          const int hh = rd_head();
          tma_store2d(&maps.ox, sb + R_V, hh * 128, s * SEG);
          tma_store2d(&maps.ox, sb + R_V + 5120, hh * 128 + 64, s * SEG);
          bulk_commit();
          bulk_wait_read0();
          if (more) mbar_arrive_remote(mapa(BAR(B_TFREE), 2));
          bulk_wait0();
          asm volatile("fence.proxy.async;" ::: "memory");
          asm volatile("red.release.gpu.global.add.u32 [%0], 1;" :: "l"(&gSync[SY_OX + (s >> 2)]) : "memory");
        }
        __syncwarp();
        PROF(7);
      } else if (more) {
        const int ln = otid() & 31, cg = rd_head() * 2 + rd_rank() - 1;
        const uint4* src = gPart + ((par(s) * 64 + cg) * 32 + (ln >> 2)) * 16 + wp * 4 + (ln & 3);
        while (__any_sync(~0u, (int)(clock() - tref) < 0)) {}
        PROF(11);
        uint4 v[4];
#pragma unroll
        for (int i = 0; i < 4; i++) v[i] = ld_relaxed128(src + i * 128);
        const int n = wp * 2 + ((ln >> 3) & 1);
        const int wi = cg < 48 ? (ln & 3) * 2 + ((ln >> 2) & 1) : (ln & 7);
        const int chk = cg >> 2, pos = chk >= NRSC ? chk : (is_u(chk) ? 7 : 0) + cls_idx(chk);
        uint32_t* dst = reinterpret_cast<uint32_t*>(gMem) + (pos * 256 + n * 32 + ((((cg & 3) * 2 + (wi >> 2)) ^ n) << 2) + (wi & 3) + (ln >> 4) * 16384);
        uint32_t* dpub = dst + ((s + 1) & 3) * 4096;
        uint32_t pubbar = mapa(BAR(B_PUB), ln < 3 ? ln : 0);
        pin(dpub); pin(pubbar);
        float a[8];
        {
#pragma unroll 1
          for (int it = 0; it < SPIN_LIMIT; it++) {
            uint32_t mn[4];
            ZERO(a, 8);
#pragma unroll
            for (int i = 0; i < 4; i++) {
              mn[i] = min(min(v[i].x, v[i].y), min(v[i].z, v[i].w));
              a[0] += bf_lo(v[i].x); a[1] += bf_lo(v[i].z); a[2] += bf_hi(v[i].x); a[3] += bf_hi(v[i].z);
              a[4] += bf_lo(v[i].y); a[5] += bf_lo(v[i].w); a[6] += bf_hi(v[i].y); a[7] += bf_hi(v[i].w);
              asm volatile("" : "+f"(a[0]), "+f"(a[1]), "+f"(a[2]), "+f"(a[3]), "+f"(a[4]), "+f"(a[5]), "+f"(a[6]), "+f"(a[7]));
              if (mn[i] == 0) v[i] = ld_relaxed128(src + i * 128);
            }
            if (__all_sync(~0u, min(min(mn[0], mn[1]), min(mn[2], mn[3])) != 0)) break;
          }
        }
        if (elect()) mbar_arrive(BAR(B_LRET));
        PROF(8);
        {
          const bool b2 = (ln & 4) != 0, b3 = (ln & 8) != 0;
          float k[4];
#pragma unroll
          for (int e = 0; e < 4; e++) k[e] = (b2 ? a[4 + e] : a[e]) + __shfl_xor_sync(~0u, b2 ? a[e] : a[4 + e], 4);
          float m0 = (b3 ? k[2] : k[0]) + __shfl_xor_sync(~0u, b3 ? k[0] : k[2], 8);
          float m1 = (b3 ? k[3] : k[1]) + __shfl_xor_sync(~0u, b3 ? k[1] : k[3], 8);
          m0 += __shfl_xor_sync(~0u, m0, 16);
          m1 += __shfl_xor_sync(~0u, m1, 16);
          const uint32_t w = nz(pack_bf16(m0, m1));
#pragma unroll
          for (int r = 0; r < NREP / 2; r++) st_relaxed32(dpub + r * 32768, w);
          if (ln == 3) mbar_arrive(BAR(B_LPUB));
          if (ln < 3) mbar_arrive_remote(pubbar);
#pragma unroll
          for (int r = 0; r < NREP / 2; r++) st_relaxed32(dst + ((s + 3) & 3) * 4096 + r * 32768, 0);
        }
        PROF(9);
        ARM();
      }
    }
    if (tid == 256) bulk_wait0();
    if (tid == 256 && rd_head() == 0 && rd_rank() == 0) TL(3);
  }
  asm volatile("barrier.cluster.arrive.aligned; barrier.cluster.wait.aligned;" ::: "memory");
}

constexpr int G_STAGES = 4;
constexpr uint32_t G_STAGE = 16384 + 32768;
#define MBW 10
#define MB1 3
#define MB2 1
constexpr int NT_F = 16 * 28, NT_B = 64, NT_W = MBW * 4, T_B = NT_F, T_W = T_B + NT_B, T_N = T_W + NT_W;
constexpr int NT_ALL = T_N + MB1 * 8 + MB2 * 16 + (16 - MBW - MB1 - MB2) * 32;
__device__ __forceinline__ int f_mb(int t) { return (t >= NT_F / 2 ? 8 : 0) + (t & 7); }
__device__ __forceinline__ int f_nb(int t) { return (t >= NT_F / 2 ? t - NT_F / 2 : t) >> 3; }
__device__ __forceinline__ void decode_n(int t, int& tile, int& part, int& lg) {
  if (t < MB1 * 8) { tile = MBW * 8 + t; part = 0; lg = 0; }
  else if (t < MB1 * 8 + MB2 * 16) { t -= MB1 * 8; tile = (MBW + MB1) * 8 + (t >> 1); part = t & 1; lg = 1; }
  else { t -= MB1 * 8 + MB2 * 16; tile = (MBW + MB1 + MB2) * 8 + (t >> 2); part = t & 3; lg = 2; }
}
constexpr uint32_t G_SMEM = G_STAGES * G_STAGE + 32768 + 256;

struct GemmMaps { CUtensorMap st[3];   CUtensorMap x, wg, wu, hid, wd, ox, wo; };

__device__ __forceinline__ void wait_counter(const unsigned* p, unsigned target) {
#pragma unroll 1
  for (int i = 0; i < (1 << 20); i++) {
    unsigned v;
    asm volatile("ld.acquire.gpu.global.u32 %0, [%1];" : "=r"(v) : "l"(p) : "memory");
    if (v >= target) break;
    __nanosleep(40);
  }
}

__global__ void __launch_bounds__(384, 1)
gemm_kernel(const __grid_constant__ GemmMaps maps, const __nv_bfloat16* __restrict__ x, const __nv_bfloat16* __restrict__ gw) {
  extern __shared__ __align__(1024) uint8_t smem[];
  const uint32_t sb = smem_u32(smem);
  const uint32_t sOut = sb + G_STAGES * G_STAGE;
  const uint32_t bars = sOut + 32768;
  const int tid = threadIdx.x, lane = tid & 31;
  const int wid = __shfl_sync(~0u, tid >> 5, 0), wg = wid >> 2, wp = wid & 3;
  volatile int* stask = reinterpret_cast<volatile int*>(smem + G_STAGES * G_STAGE + 32768 + 160);
  volatile int* sdesc = stask + 4;
  if (tid == 0) {
    for (int i = 0; i < G_STAGES; i++) { mbar_init(bars + 8 * i, 1); mbar_init(bars + 32 + 8 * i, 8); }
    for (int i = 0; i < 2; i++) {
      mbar_init(bars + 64 + 8 * i, 1); mbar_init(bars + 80 + 8 * i, 8); mbar_init(bars + 96 + 8 * i, 1);
      mbar_init(bars + 112 + 8 * i, 1); mbar_init(bars + 128 + 8 * i, 1);
    }
    mbar_init(bars + 144, 8);
    fence_async();
  }
  __syncthreads();
  if (wg == 2) {
    asm volatile("setmaxnreg.dec.sync.aligned.u32 40;");
    if (wp == 0) {
      int it = 0, task = 0;
#pragma unroll 1
      for (int n = 0;; n++) {
        if (task >= T_W) gwait(bars + 144, (n - 1) & 1);
        if (lane == 0) task = (int)atomicAdd(&gSync[SY_QUEUE], 1u);
        task = __shfl_sync(~0u, task, 0);
        const CUtensorMap *ta = &maps.ox, *tb = &maps.wo, *tb2 = &maps.wo;
        int mb = 0, c0 = 0, c2 = 0, nk = HD / 64, k0 = 0;
        if (task < T_B) {
          mb = f_mb(task); c0 = c2 = f_nb(task) * 128; nk = DM / 64; ta = &maps.x; tb = &maps.wg; tb2 = &maps.wu;
        } else if (task < T_W) {
          mb = (task - T_B) >> 2; c0 = (task & 3) * 256; c2 = c0 + 128; nk = FF / 64; ta = &maps.hid; tb = tb2 = &maps.wd;
          if (lane == 0) wait_counter(&gSync[SY_HID + mb], 56);
        } else if (task < NT_ALL) {
          if (task < T_N) { mb = (task - T_W) >> 2; c0 = (task & 3) * 256; c2 = c0 + 128; }
          else {
            int tile, part, lg;
            decode_n(task - T_N, tile, part, lg);
            mb = tile >> 3; c0 = (tile & 7) * 128; nk >>= lg; k0 = part * nk;
          }
          if (lane < 3) wait_counter(&gSync[lane == 0 ? SY_OX + mb : (lane == 1 ? SY_GATE : SY_B + mb * 4 + (c0 >> 8))], lane == 0 ? 4 * NH : (lane == 1 ? S_LEN / 8 : 4));
        }
        __syncwarp();
        if (lane == 0) {
          gwait(bars + 80 + 8 * (n & 1), ((n >> 1) & 1) ^ 1);
          if (task <= NT_ALL) TL(16 + task);
          if (n == 0) TL(1800 + blockIdx.x);
          stask[n & 1] = task;
          mbar_arrive(bars + 64 + 8 * (n & 1));
          if (task < NT_ALL) {
            asm volatile("fence.proxy.async;" ::: "memory");
#pragma unroll 1
            for (int k = k0; k < k0 + nk; k++, it++) {
              const int st = it % G_STAGES;
              gwait(bars + 32 + 8 * st, ((it / G_STAGES) & 1) ^ 1);
              const uint32_t d = sb + st * G_STAGE, fb = bars + 8 * st;
              mbar_expect(fb, task < T_N ? G_STAGE : 32768u);
              tma_load2d(d, ta, k * 64, mb * 128, fb);
              tma_load2d(d + 16384, tb, c0, k * 64, fb);
              tma_load2d(d + 24576, tb, c0 + 64, k * 64, fb);
              if (task < T_N) {
                tma_load2d(d + 32768, tb2, c2, k * 64, fb);
                tma_load2d(d + 40960, tb2, c2 + 64, k * 64, fb);
              }
            }
          }
        }
        __syncwarp();
        if (task >= NT_ALL) break;
      }
    } else {
#pragma unroll 1
      while (true) {
        int blk = 0;
        if (lane == 0) blk = (int)atomicAdd(&gSync[SY_GQ], 1u);
        blk = __shfl_sync(~0u, blk, 0);
        if (blk >= S_LEN / 8) break;
        const int row = blk * 8 + (lane >> 2);
        const uint4* xr = reinterpret_cast<const uint4*>(x + (size_t)row * DM) + (lane & 3);
        const uint4* gr = reinterpret_cast<const uint4*>(gw) + (lane & 3);
        float g = 0.f;
#pragma unroll 2
        for (int i = 0; i < 32; i++) {
          const uint4 a = xr[i * 4], b = gr[i * 4];
          g += bf_lo(a.x) * bf_lo(b.x) + bf_hi(a.x) * bf_hi(b.x) + bf_lo(a.y) * bf_lo(b.y) + bf_hi(a.y) * bf_hi(b.y) +
               bf_lo(a.z) * bf_lo(b.z) + bf_hi(a.z) * bf_hi(b.z) + bf_lo(a.w) * bf_lo(b.w) + bf_hi(a.w) * bf_hi(b.w);
        }
        g += __shfl_xor_sync(~0u, g, 1); g += __shfl_xor_sync(~0u, g, 2);
        if ((lane & 3) == 0) gGate[row] = rcp(1.0f + ex2(g * -1.4426950408889634f));
        __threadfence();
        __syncwarp();
        if (lane == 0) asm volatile("red.release.gpu.global.add.u32 [%0], 1;" :: "l"(&gSync[SY_GATE]) : "memory");
      }
      if (wp < 3) {
        if (lane == 0) {
          const int w = wp - 1;
#pragma unroll 1
          for (int n = 0;; n++) {
            gwait(bars + 112 + 8 * w, n & 1);
            const int id = sdesc[w * 4], c0 = sdesc[w * 4 + 1], c1 = sdesc[w * 4 + 2], flag = sdesc[w * 4 + 3];
            if (id < 0) break;
            tma_store2d(&maps.st[id], sOut + w * 8192, c0, c1);
            tma_store2d(&maps.st[id], sOut + 16384 + w * 8192, c0 + 64, c1);
            bulk_commit();
            bulk_wait_read0();
            mbar_arrive(bars + 128 + 8 * w);
            bulk_wait0();
            if (flag >= 0) {
              asm volatile("fence.proxy.async;" ::: "memory");
              asm volatile("red.release.gpu.global.add.u32 [%0], 1;" :: "l"(&gSync[flag]) : "memory");
            }
          }
        }
      } else {
        asm volatile("griddepcontrol.wait;" ::: "memory");
        for (int i = blockIdx.x * 32 + lane; i < 2 * 64 * 32 * 16; i += gridDim.x * 32) gPart[i] = make_uint4(0, 0, 0, 0);
        for (int i = blockIdx.x * 32 + lane; i < NREP * 4 * 1024; i += gridDim.x * 32) gMem[i] = make_uint4(0, 0, 0, 0);
      }
    }
  } else {
    asm volatile("setmaxnreg.inc.sync.aligned.u32 232;");
    int it = 0, nb_ld = 0, nst = 0;
    const int r = wg * 64 + wp * 16 + (lane & 7) + ((lane >> 3) & 1) * 8;
    const uint32_t oa0 = sOut + r * 128, osw = (lane >> 4) ^ (r & 7);
    auto stage_acquire = [&]() { gwait(bars + 128 + 8 * wg, (nst & 1) ^ 1); };
    auto stage_emit = [&](int id, int c0, int c1, int flag) {
      fence_async();
      bar_sync(1 + wg, 128);
      if ((tid & 127) == 0) {
        sdesc[wg * 4] = id; sdesc[wg * 4 + 1] = c0; sdesc[wg * 4 + 2] = c1; sdesc[wg * 4 + 3] = flag;
        mbar_arrive(bars + 112 + 8 * wg);
      }
      nst++;
    };
    auto load_b = [&](int c0, int c1) {
      if ((tid & 127) == 0) {
        asm volatile("fence.proxy.async;" ::: "memory");
        mbar_expect(bars + 96 + 8 * wg, 16384);
        tma_load2d(sOut + wg * 8192, &maps.st[1], c0, c1, bars + 96 + 8 * wg);
        tma_load2d(sOut + 16384 + wg * 8192, &maps.st[1], c0 + 64, c1, bars + 96 + 8 * wg);
      }
      __syncwarp();
    };
    auto write_tile = [&](const float* a, bool mix, float g0, float g1) {
      if (mix) { gwait(bars + 96 + 8 * wg, nb_ld & 1); nb_ld++; }
#pragma unroll
      for (int j = 0; j < 8; j++) {
        uint32_t v[4], bv[4];
        const uint32_t oa = oa0 + (j >> 2) * 16384 + ((osw ^ ((j & 3) * 2)) << 4);
        if (mix) ldsm4(bv, oa);
#pragma unroll
        for (int q = 0; q < 4; q++) {
          const int i = j * 8 + q * 2;
          const float g = (q & 1) ? g1 : g0;
          v[q] = mix ? pack_bf16(g * a[i] + (1.0f - g) * bf_lo(bv[q]), g * a[i + 1] + (1.0f - g) * bf_hi(bv[q])) : pack_bf16(a[i], a[i + 1]);
        }
        stsm4(oa, v[0], v[1], v[2], v[3]);
      }
    };
#pragma unroll 1
    for (int n = 0;; n++) {
      gwait(bars + 64 + 8 * (n & 1), (n >> 1) & 1);
      const int task = stask[n & 1];
      __syncwarp();
      if (lane == 0) mbar_arrive(bars + 80 + 8 * (n & 1));
      if (task >= NT_ALL) {
        stage_acquire();
        stage_emit(-1, 0, 0, -1);
        break;
      }
      if (tid == 0) TL(2048 + task);
      if (task < T_N) {
        const bool isF = task < T_B, isA = task >= T_W;
        const int mb = isF ? f_mb(task) : (task - (isA ? T_W : T_B)) >> 2;
        const int c0 = isF ? f_nb(task) * 128 : (task & 3) * 256, c1 = mb * 128 + wg * 64;
        const int nk = isF ? DM / 64 : (isA ? HD / 64 : FF / 64);
        if (isA) { stage_acquire(); load_b(c0, c1); }
        float acc[128];
        ZERO(acc, 128);
#pragma unroll 1
        for (int k = 0; k < nk; k++, it++) {
          const int st = it % G_STAGES;
          gwait(bars + 8 * st, (it / G_STAGES) & 1);
          const uint32_t d16 = ((sb + st * G_STAGE) & 0x3FFFF) >> 4;
          WG_FENCE();
#pragma unroll
          for (int j = 0; j < 4; j++) wg_ss256<0, 1>(acc, mkd(d16 + wg * 512, j * 32, 0, 1024, 1), mkd(d16, 16384 + j * 2048, 8192, 1024, 1), 1);
          WG_COMMIT();
          if (k > 0) { WG_WAIT(1); if (lane == 0) mbar_arrive(bars + 32 + 8 * ((it - 1) % G_STAGES)); }
        }
        float g0 = 0.f, g1 = 0.f;
        if (isA) { g0 = __ldcg(&gGate[c1 + wp * 16 + (lane >> 2)]); g1 = __ldcg(&gGate[c1 + wp * 16 + (lane >> 2) + 8]); }
        else stage_acquire();
        WG_WAIT(0);
        if (lane == 0) mbar_arrive(bars + 32 + 8 * ((it - 1) % G_STAGES));
        if (isF) {
#pragma unroll
          for (int i = 0; i < 64; i++) acc[i] = acc[i] * rcp(1.0f + ex2(acc[i] * -1.4426950408889634f)) * acc[64 + i];
          write_tile(acc, false, 0.f, 0.f);
          stage_emit(0, c0, c1, SY_HID + mb);
        } else {
          const int flag = isA ? -1 : SY_B + (task - T_B);
          write_tile(acc, isA, g0, g1);
          stage_emit(isA ? 2 : 1, c0, c1, flag);
          stage_acquire();
          if (isA) load_b(c0 + 128, c1);
          write_tile(acc + 64, isA, g0, g1);
          stage_emit(isA ? 2 : 1, c0 + 128, c1, flag);
        }
      } else {
        int tile, part, lg;
        decode_n(task - T_N, tile, part, lg);
        const int c0 = (tile & 7) * 128, c1 = (tile >> 3) * 128 + wg * 64, nk = (HD / 64) >> lg, nparts = 1 << lg;
        if (part + 1 == nparts) { stage_acquire(); load_b(c0, c1); }
        float acc[64];
        ZERO(acc, 64);
#pragma unroll 1
        for (int k = 0; k < nk; k++, it++) {
          const int st = it % G_STAGES;
          gwait(bars + 8 * st, (it / G_STAGES) & 1);
          const uint32_t d16 = ((sb + st * G_STAGE) & 0x3FFFF) >> 4;
          WG_FENCE();
#pragma unroll
          for (int j = 0; j < 4; j++) wg_ss128<0, 1>(acc, mkd(d16 + wg * 512, j * 32, 0, 1024, 1), mkd(d16, 16384 + j * 2048, 8192, 1024, 1), 1);
          WG_COMMIT();
          if (k > 0) { WG_WAIT(1); if (lane == 0) mbar_arrive(bars + 32 + 8 * ((it - 1) % G_STAGES)); }
        }
        const float g0 = __ldcg(&gGate[c1 + wp * 16 + (lane >> 2)]), g1 = __ldcg(&gGate[c1 + wp * 16 + (lane >> 2) + 8]);
        WG_WAIT(0);
        if (lane == 0) mbar_arrive(bars + 32 + 8 * ((it - 1) % G_STAGES));
        if (tid == 0) TL(4096 + task);
        if (part + 1 < nparts) {
          float4* tp = gTail + (tile * 3 + part) * 4096 + tid;
#pragma unroll
          for (int j = 0; j < 16; j++) __stcg(tp + j * 256, make_float4(acc[j * 4], acc[j * 4 + 1], acc[j * 4 + 2], acc[j * 4 + 3]));
          __syncwarp();
          if (lane == 0) { __threadfence(); asm volatile("red.relaxed.gpu.global.add.u32 [%0], 1;" :: "l"(&gTailFlag[tile * 8 + wid]) : "memory"); }
        } else {
          if (nparts > 1) {
            if (lane == 0) { wait_counter(&gTailFlag[tile * 8 + wid], nparts - 1); gTailFlag[tile * 8 + wid] = 0; }
            __syncwarp();
            const float4* tp = gTail + tile * 3 * 4096 + tid;
            if (nparts == 2) {
#pragma unroll
              for (int j = 0; j < 16; j++) {
                const float4 t = __ldcg(tp + j * 256);
                acc[j * 4] += t.x; acc[j * 4 + 1] += t.y; acc[j * 4 + 2] += t.z; acc[j * 4 + 3] += t.w;
              }
            } else {
#pragma unroll
              for (int j = 0; j < 16; j++) {
                const float4 t = __ldcg(tp + j * 256), u = __ldcg(tp + 4096 + j * 256), w = __ldcg(tp + 8192 + j * 256);
                acc[j * 4] += t.x + u.x + w.x; acc[j * 4 + 1] += t.y + u.y + w.y; acc[j * 4 + 2] += t.z + u.z + w.z; acc[j * 4 + 3] += t.w + u.w + w.w;
              }
            }
          }
          write_tile(acc, true, g0, g1);
          stage_emit(2, c0, c1, -1);
        }
      }
      if (lane == 0) mbar_arrive(bars + 144);
      if (tid == 0) TL(5120 + task);
    }
  }
}

typedef CUresult (*EncodeFn)(CUtensorMap*, CUtensorMapDataType, cuuint32_t, void*, const cuuint64_t*, const cuuint64_t*,
                             const cuuint32_t*, const cuuint32_t*, CUtensorMapInterleave, CUtensorMapSwizzle,
                             CUtensorMapL2promotion, CUtensorMapFloatOOBfill);

void make_map(EncodeFn fn, CUtensorMap* m, const void* ptr, uint64_t inner, uint64_t outer, uint32_t bi, uint32_t bo,
              CUtensorMapSwizzle swz) {
  cuuint64_t dims[2] = {inner, outer};
  cuuint64_t strides[1] = {inner * 2};
  cuuint32_t box[2] = {bi, bo};
  cuuint32_t es[2] = {1, 1};
  fn(m, CU_TENSOR_MAP_DATA_TYPE_BFLOAT16, 2, const_cast<void*>(ptr), dims, strides, box, es, CU_TENSOR_MAP_INTERLEAVE_NONE, swz,
     CU_TENSOR_MAP_L2_PROMOTION_L2_256B, CU_TENSOR_MAP_FLOAT_OOB_FILL_NONE);
}

}

extern "C" void kernel_launch(void* const* d_in, const int* in_sizes, int n_in, void* d_out, int out_size) {
  (void)in_sizes; (void)n_in; (void)out_size;
  const __nv_bfloat16* x = (const __nv_bfloat16*)d_in[0];
  const __nv_bfloat16* mem0 = (const __nv_bfloat16*)d_in[1];
  const void* Wq = d_in[2]; const void* Wk = d_in[3]; const void* Wv = d_in[4]; const void* Wo = d_in[5];
  const void* Wg = d_in[8]; const void* Wu = d_in[9]; const void* Wd = d_in[10];
  const __nv_bfloat16* gw = (const __nv_bfloat16*)d_in[11];

  void* fnp = nullptr;
  cudaDriverEntryPointQueryResult qr;
  cudaGetDriverEntryPoint("cuTensorMapEncodeTiled", &fnp, cudaEnableDefault, &qr);
  EncodeFn fn = (EncodeFn)fnp;
  void *pOx, *pHid, *pB;
  cudaGetSymbolAddress(&pB, gB);
  cudaGetSymbolAddress(&pOx, gOx);
  cudaGetSymbolAddress(&pHid, gHid);

  const CUtensorMapSwizzle S128 = CU_TENSOR_MAP_SWIZZLE_128B, S64 = CU_TENSOR_MAP_SWIZZLE_64B;
  RecMaps rm;
  make_map(fn, &rm.w[0], Wq, HD, DM, 64, 64, S128);
  make_map(fn, &rm.w[1], Wk, HD, DM, 64, 64, S128);
  make_map(fn, &rm.w[2], Wv, HD, DM, 64, 64, S128);
  make_map(fn, &rm.wo, Wo, DM, HD, 64, 128, S128);
  make_map(fn, &rm.wo_half, Wo, DM, HD, 32, 64, S64);
  {
    cuuint64_t dims[3] = {64, (cuuint64_t)S_LEN, 16};
    cuuint64_t strides[2] = {DM * 2, 128};
    cuuint32_t box[3] = {64, 32, 2};
    cuuint32_t es[3] = {1, 1, 1};
    fn(&rm.x2, CU_TENSOR_MAP_DATA_TYPE_BFLOAT16, 3, (void*)x, dims, strides, box, es, CU_TENSOR_MAP_INTERLEAVE_NONE, S128,
       CU_TENSOR_MAP_L2_PROMOTION_L2_256B, CU_TENSOR_MAP_FLOAT_OOB_FILL_NONE);
    box[2] = 3;
    fn(&rm.x3, CU_TENSOR_MAP_DATA_TYPE_BFLOAT16, 3, (void*)x, dims, strides, box, es, CU_TENSOR_MAP_INTERLEAVE_NONE, S128,
       CU_TENSOR_MAP_L2_PROMOTION_L2_256B, CU_TENSOR_MAP_FLOAT_OOB_FILL_NONE);
    box[2] = 1;
    fn(&rm.x1, CU_TENSOR_MAP_DATA_TYPE_BFLOAT16, 3, (void*)x, dims, strides, box, es, CU_TENSOR_MAP_INTERLEAVE_NONE, S128,
       CU_TENSOR_MAP_L2_PROMOTION_L2_256B, CU_TENSOR_MAP_FLOAT_OOB_FILL_NONE);
  }
  make_map(fn, &rm.ox, pOx, HD, S_LEN, 64, 32, S128);
  GemmMaps gm;
  make_map(fn, &gm.x, x, DM, S_LEN, 64, 128, S128);
  make_map(fn, &gm.wg, Wg, FF, DM, 64, 64, S128);
  make_map(fn, &gm.wu, Wu, FF, DM, 64, 64, S128);
  make_map(fn, &gm.st[0], pHid, FF, S_LEN, 64, 64, S128);
  make_map(fn, &gm.hid, pHid, FF, S_LEN, 64, 128, S128);
  make_map(fn, &gm.wd, Wd, DM, FF, 64, 64, S128);
  make_map(fn, &gm.st[1], pB, DM, S_LEN, 64, 64, S128);
  make_map(fn, &gm.ox, pOx, HD, S_LEN, 64, 128, S128);
  make_map(fn, &gm.wo, Wo, DM, HD, 64, 64, S128);
  make_map(fn, &gm.st[2], d_out, DM, S_LEN, 64, 64, S128);

  cudaFuncSetAttribute(rec_kernel, cudaFuncAttributeMaxDynamicSharedMemorySize, REC_SMEM + (REC_PROF ? 768 : 0));
  cudaFuncSetAttribute(gemm_kernel, cudaFuncAttributeMaxDynamicSharedMemorySize, G_SMEM);

  rec_kernel<<<dim3(3, 32), 384, REC_SMEM + (REC_PROF ? 768 : 0), cudaStreamPerThread>>>(rm, mem0, x, (const __nv_bfloat16*)Wo);
  {
    cudaLaunchConfig_t cfg = {};
    cfg.gridDim = dim3(132); cfg.blockDim = dim3(384); cfg.dynamicSmemBytes = G_SMEM; cfg.stream = cudaStreamPerThread;
    cudaLaunchAttribute at[1];
    at[0].id = cudaLaunchAttributeProgrammaticStreamSerialization;
    at[0].val.programmaticStreamSerializationAllowed = 1;
    cfg.attrs = at; cfg.numAttrs = 1;
    cudaLaunchKernelEx(&cfg, gemm_kernel, gm, x, gw);
  }
}
```
